```python
import torch

def _softmax(x, axis=-1):
    return torch.softmax(x, dim=axis)
def _gelu(x):
    return torch.nn.functional.gelu(x, approximate="tanh")
def _silu(x):
    return torch.nn.functional.silu(x)
def _sigmoid(x):
    return torch.sigmoid(x)
def _layernorm(x, axis=-1, eps=1e-5):
    m = x.mean(dim=axis, keepdim=True)
    v = x.var(dim=axis, keepdim=True, unbiased=False)
    return (x - m) / torch.sqrt(v + eps)
def _scatter_add(tgt, idx, src, axis=0):
    return tgt.clone().index_add_(axis, idx, src)
def _segment_sum(src, seg, n):
    out = torch.zeros((n,) + src.shape[1:], dtype=src.dtype)
    return out.index_add_(0, seg, src)
def _pad(x, pw):
    flat = tuple(v for pair in reversed(pw) for v in pair)
    return torch.nn.functional.pad(x, flat)

kernel_name = 'sequential_preLN__ssm_conv_h3__mixer_s_mlp__prompt'

def setup_inputs():

    _w = (lambda a: (lambda t: t.to(torch.bfloat16) if t.is_floating_point() else t)(torch.as_tensor(a)))
    def _A_setup():
        B, S, D = 1, 2048, 640
        ks = 4
        return {
            "q": _w((lambda *s: torch.randn(*s, dtype=torch.bfloat16) * 0.05)(B, S, D)),
            "k": _w((lambda *s: torch.randn(*s, dtype=torch.bfloat16) * 0.4)(B, S, D)),
            "v": _w((lambda *s: torch.randn(*s, dtype=torch.bfloat16) * 0.4)(B, S, D)),
            "shift_k": _w((lambda *s: torch.randn(*s, dtype=torch.bfloat16) * 0.4)(D, ks) * 0.5),
            "ssm_k": _w((lambda *s: torch.randn(*s, dtype=torch.bfloat16) * 0.4)(D, S) * (1.0 / S ** 0.5)),
            "ssm_D": _w((lambda *s: torch.randn(*s, dtype=torch.bfloat16) * 0.4)(D)),
        }
    _A_in = _A_setup()

    def _B_setup():
        B, S, D, F = 1, 2048, 640, 1728
        return {
            "x":  _w((lambda *s: torch.randn(*s, dtype=torch.bfloat16) * 0.05)(B, S, D)),
            "w1": _w((lambda *s: torch.randn(*s, dtype=torch.bfloat16) * 3.2)(D, D) * (D ** -0.5)),
            "w2": _w((lambda *s: torch.randn(*s, dtype=torch.bfloat16) * 3.2)(D, D) * (D ** -0.5)),
            "w3": _w((lambda *s: torch.randn(*s, dtype=torch.bfloat16) * 3.2)(D, F) * (D ** -0.5)),
            "w4": _w((lambda *s: torch.randn(*s, dtype=torch.bfloat16) * 3.2)(F, D) * (F ** -0.5)),
        }
    _B_in = _B_setup()

    return {
        "A_q": _A_in["q"],
        "A_k": _A_in["k"],
        "A_v": _A_in["v"],
        "A_shift_k": _A_in["shift_k"],
        "A_ssm_k": _A_in["ssm_k"],
        "A_ssm_D": _A_in["ssm_D"],
        "B_x": _B_in["x"],
        "B_w1": _B_in["w1"],
        "B_w2": _B_in["w2"],
        "B_w3": _B_in["w3"],
        "B_w4": _B_in["w4"],
    }

def reference(A_q, A_k, A_v, A_shift_k, A_ssm_k, A_ssm_D, B_x, B_w1, B_w2, B_w3, B_w4):
    def _A_ref(q, k, v, shift_k, ssm_k, ssm_D):
        B, S, D = q.shape
        ks = shift_k.shape[-1]
        k_pad = _pad(k, ((0, 0), (ks - 1, 0), (0, 0)))
        k_shift = torch.zeros_like(k)
        for t in range(ks):
            k_shift = k_shift + k_pad[:, t:t + S, :] * shift_k[:, ks - 1 - t][None, None, :]
        kv = k_shift * v
        L = 2 * S
        kv_pad = _pad(kv, ((0, 0), (0, S), (0, 0)))
        kf_pad = _pad(ssm_k, ((0, 0), (0, S)))
        kv_f = (lambda x, axes=(-2,-1): torch.fft.rfft2(x.float(), dim=axes))(kv_pad[:, None, :, :], axes=(1, 2))
        kf_f = (lambda x, axes=(-2,-1): torch.fft.rfft2(x.float(), dim=axes))(kf_pad[:, None, :], axes=(1, 2))
        kf_f = (lambda x, *d: x.permute(*d))(kf_f, 1, 2, 0)
        y_f = kv_f * kf_f[None, :, :, :]
        y = (lambda x, s, axes=(-2,-1): torch.fft.irfft2(x, s=s, dim=axes).to(torch.bfloat16))(y_f, (1, L), axes=(1, 2))[:, 0, :S, :]
        y = y + kv * ssm_D[None, None, :]
        return q * y

    def _B_ref(x, w1, w2, w3, w4):
        B, S, D = x.shape
        h = _gelu(_layernorm(x, axis=-1) @ w1)
        c = D // 4
        g0 = _pad(h[:, :, 0*c:1*c], ((0, 0), (1, 0), (0, 0)))[:, :S, :]
        g1 = _pad(h[:, :, 1*c:2*c], ((0, 0), (0, 1), (0, 0)))[:, 1:, :]
        g2 = _pad(h[:, :, 2*c:3*c], ((0, 0), (2, 0), (0, 0)))[:, :S, :]
        g3 = _pad(h[:, :, 3*c:   ], ((0, 0), (0, 2), (0, 0)))[:, 2:, :]
        hs = torch.concatenate([g0, g1, g2, g3], axis=-1) @ w2
        x1 = x + hs
        h2 = _gelu(_layernorm(x1, axis=-1) @ w3) @ w4
        return x1 + h2

    x = A_q
    h = x + _A_ref(_layernorm(x, axis=-1), A_k, A_v, A_shift_k, A_ssm_k, A_ssm_D)
    h2 = h + _B_ref(_layernorm(h, axis=-1), B_w1, B_w2, B_w3, B_w4)
    return h2
```

```cpp
#include <cuda_runtime.h>
#include <cuda.h>
#include <cuda_bf16.h>
#include <stdint.h>

namespace {

constexpr int S = 2048, D = 640, FF = 1728;
constexpr int NCTA = 130, NTHR = 512;
constexpr float EPS = 1e-5f;
#define SSM_DELAY 2000

constexpr int NWB = 15;
constexpr int OFF_W = 0;
constexpr int OFF_X = NWB * 8192;
constexpr int XSLOT = 20480;
constexpr int OFF_ST = OFF_X + 4 * XSLOT;
constexpr int OFF_MISC = OFF_ST + 20480;
constexpr int OFF_BAR = OFF_MISC;
constexpr int OFF_RP = OFF_MISC + 640;
constexpr int OFF_RP3 = OFF_RP + 1280;
constexpr int OFF_RQ = OFF_RP3 + 1280;
constexpr int OFF_PS = OFF_RQ + 640;
constexpr int OFF_PQ = OFF_PS + 640;
constexpr int OFF_CS = OFF_PQ + 640;
constexpr int SMEM_BYTES = 232448;
static_assert(OFF_CS + 384 <= SMEM_BYTES, "smem");
constexpr int OFF_KV = 0;
constexpr int OFF_QT = 73728;
constexpr int OFF_YT = OFF_X + 3 * XSLOT;
constexpr int CB = 94208;
constexpr int PBYTES = 8448, XBYTES = 4352, XLBO = 2176, RBYTES = 21504;
constexpr int OFF_P = CB, OFF_XC = CB + 5 * PBYTES, OFF_RED = OFF_XC + 5 * XBYTES;
static_assert(OFF_RED + 3 * RBYTES <= OFF_MISC, "conv overlay");
constexpr int WFREE = 9;
constexpr int B_FW = 0, B_EW = 15, B_FX = 30, B_EX = 38, B_XC = 42, B_CD = 47, B_QT = 48, B_QS = 49, B_YT = 50, B_TD = 51,
              B_RP = 52, B_RP3 = 53, B_TA = 54, B_TE = 55  , B_DUMMY = 60, NBAR = 61;
#define BAR(i) (sb + OFF_BAR + 8 * (i))

struct alignas(64) Params {
  CUtensorMap w1, w2, w3, w4, kv, q80, y80, h, h1, h1n, x1s, x1l, hs, hl, out;
  const __nv_bfloat16 *q, *k, *v, *shk, *ssm, *ssd, *w1p, *w2p, *w3p, *w4p;
};

constexpr int SP = S + 128;
__device__ __align__(1024) __nv_bfloat16 g_kvT[D * S];
__device__ __align__(1024) __nv_bfloat16 g_yT[D * S];
__device__ __align__(1024) __nv_bfloat16 g_h[S * D];
__device__ __align__(1024) __nv_bfloat16 g_h1[S * D];
__device__ __align__(1024) __nv_bfloat16 g_x1[S * D];
__device__ __align__(1024) __nv_bfloat16 g_hid[S * FF];
__device__ __align__(128) float2 g_st[3][5][SP];
__device__ __align__(128) float g_cs[FF + D];
__device__ __align__(128) unsigned g_cnt[192 * 32];
__device__ unsigned g_epoch;
constexpr int C_BAR1 = 0, C_BAR2 = 1, C_T = 2, C_G1 = 28, C_G2 = 54, C_G3 = 80, C_SQ = 94, C_SH = 120, C_SX = 146;
#define CNT(i) (&g_cnt[(i) * 32])
#define PROFT(i) do { } while (0)
#define PROF0(i) do { } while (0)
#define TST 0

__device__ __forceinline__ uint32_t s2u(const void* p) { return (uint32_t)__cvta_generic_to_shared(p); }
__device__ __forceinline__ void mbar_init(uint32_t b, int c) { asm volatile("mbarrier.init.shared::cta.b64 [%0], %1;" ::"r"(b), "r"(c) : "memory"); }
__device__ __forceinline__ void mbar_expect(uint32_t b, int bytes) { asm volatile("mbarrier.arrive.expect_tx.shared::cta.b64 _, [%0], %1;" ::"r"(b), "r"(bytes) : "memory"); }
__device__ __forceinline__ void mbar_arrive(uint32_t b) { asm volatile("mbarrier.arrive.shared::cta.b64 _, [%0];" ::"r"(b) : "memory"); }
__device__ __forceinline__ void mbar_arrive_n(uint32_t b, int n) { asm volatile("mbarrier.arrive.shared::cta.b64 _, [%0], %1;" ::"r"(b), "r"(n) : "memory"); }
__device__ __forceinline__ bool mbar_try(uint32_t b, uint32_t parity) {
  uint32_t ok;
  asm volatile("{\n.reg .pred p;\nmbarrier.try_wait.parity.shared::cta.b64 p, [%1], %2;\nselp.u32 %0, 1, 0, p;\n}" : "=r"(ok) : "r"(b), "r"(parity) : "memory");
  return ok;
}
__device__ __forceinline__ void mbar_wait(uint32_t b, uint32_t parity) {
  if (mbar_try(b, parity)) return;
  int it = 0;
  while (!mbar_try(b, parity)) { if (++it > (1 << 22)) __trap(); }
}
__device__ __forceinline__ void wait_cnt(const unsigned* p, unsigned target) {
  unsigned v; int it = 0;
  while (true) {
    asm volatile("ld.acquire.gpu.global.u32 %0, [%1];" : "=r"(v) : "l"(p) : "memory");
    if ((int)(v - target) >= 0) break;
    if (++it > (1 << 22)) __trap();
  }
}
__device__ __forceinline__ void red_release(unsigned* p) { asm volatile("red.release.gpu.global.add.u32 [%0], 1;" ::"l"(p) : "memory"); }
__device__ __forceinline__ void fence_async_all() { asm volatile("fence.proxy.async;" ::: "memory"); }
__device__ __forceinline__ void fence_async_smem() { asm volatile("fence.proxy.async.shared::cta;" ::: "memory"); }
__device__ __forceinline__ void bar_sync(int id, int n) { asm volatile("bar.sync %0, %1;" ::"r"(id), "r"(n) : "memory"); }
__device__ __forceinline__ bool elect_one() {
  uint32_t e; asm volatile("{\n.reg .pred p;\nelect.sync _|p, 0xffffffff;\nselp.u32 %0, 1, 0, p;\n}" : "=r"(e)); return e;
}
__device__ __forceinline__ void tma_load(uint32_t dst, const CUtensorMap* tm, uint32_t bar, int c0, int c1) {
  asm volatile("cp.async.bulk.tensor.2d.shared::cluster.global.mbarrier::complete_tx::bytes [%0], [%1, {%3, %4}], [%2];"
               ::"r"(dst), "l"(tm), "r"(bar), "r"(c0), "r"(c1) : "memory");
}
__device__ __forceinline__ void tma_store(const CUtensorMap* tm, uint32_t src, int c0, int c1) {
  asm volatile("cp.async.bulk.tensor.2d.global.shared::cta.bulk_group [%0, {%2, %3}], [%1];" ::"l"(tm), "r"(src), "r"(c0), "r"(c1) : "memory");
}
__device__ __forceinline__ void bulk_load(uint32_t dst, const void* src, int bytes, uint32_t bar) {
  asm volatile("cp.async.bulk.shared::cluster.global.mbarrier::complete_tx::bytes [%0], [%1], %2, [%3];" ::"r"(dst), "l"(src), "r"(bytes), "r"(bar) : "memory");
}
__device__ __forceinline__ void bulk_store(void* dst, uint32_t src, int bytes) {
  asm volatile("cp.async.bulk.global.shared::cta.bulk_group [%0], [%1], %2;" ::"l"(dst), "r"(src), "r"(bytes) : "memory");
}
__device__ __forceinline__ void bulk_prefetch(const void* src, int bytes) { asm volatile("cp.async.bulk.prefetch.L2.global [%0], %1;" ::"l"(src), "r"(bytes) : "memory"); }
__device__ __forceinline__ void bulk_commit() { asm volatile("cp.async.bulk.commit_group;" ::: "memory"); }
__device__ __forceinline__ void bulk_wait0() { asm volatile("cp.async.bulk.wait_group 0;" ::: "memory"); }
__device__ __forceinline__ void bulk_wait0_read() { asm volatile("cp.async.bulk.wait_group.read 0;" ::: "memory"); }
__device__ __forceinline__ void wg_fence() { asm volatile("wgmma.fence.sync.aligned;" ::: "memory"); }
__device__ __forceinline__ void wg_commit() { asm volatile("wgmma.commit_group.sync.aligned;" ::: "memory"); }
template <int N> __device__ __forceinline__ void wg_wait() { asm volatile("wgmma.wait_group.sync.aligned %0;" ::"n"(N) : "memory"); }
__device__ __forceinline__ uint64_t mkdesc(uint32_t addr, uint32_t lbo, uint32_t sbo, uint32_t swz) {
  return (uint64_t)((addr & 0x3FFFF) >> 4) | ((uint64_t)(lbo >> 4) << 16) | ((uint64_t)(sbo >> 4) << 32) | ((uint64_t)swz << 62);
}
__device__ __forceinline__ uint32_t lds32(uint32_t a) { uint32_t v; asm volatile("ld.shared.b32 %0, [%1];" : "=r"(v) : "r"(a) : "memory"); return v; }
__device__ __forceinline__ float4 lds128f(uint32_t a) { float4 v; asm volatile("ld.shared.v4.f32 {%0,%1,%2,%3}, [%4];" : "=f"(v.x), "=f"(v.y), "=f"(v.z), "=f"(v.w) : "r"(a) : "memory"); return v; }
__device__ __forceinline__ float2 lds64f(uint32_t a) { float2 v; asm volatile("ld.shared.v2.f32 {%0,%1}, [%2];" : "=f"(v.x), "=f"(v.y) : "r"(a) : "memory"); return v; }
__device__ __forceinline__ void sts128f(uint32_t a, float x, float y, float z, float w) { asm volatile("st.shared.v4.f32 [%0], {%1,%2,%3,%4};" ::"r"(a), "f"(x), "f"(y), "f"(z), "f"(w) : "memory"); }
__device__ __forceinline__ void sts128u(uint32_t a, uint32_t x, uint32_t y, uint32_t z, uint32_t w) { asm volatile("st.shared.v4.b32 [%0], {%1,%2,%3,%4};" ::"r"(a), "r"(x), "r"(y), "r"(z), "r"(w) : "memory"); }
__device__ __forceinline__ void sts64f(uint32_t a, float x, float y) { asm volatile("st.shared.v2.f32 [%0], {%1,%2};" ::"r"(a), "f"(x), "f"(y) : "memory"); }
__device__ __forceinline__ void ldsm4t(uint32_t a, uint32_t& r0, uint32_t& r1, uint32_t& r2, uint32_t& r3) {
  asm volatile("ldmatrix.sync.aligned.m8n8.x4.trans.shared.b16 {%0,%1,%2,%3}, [%4];" : "=r"(r0), "=r"(r1), "=r"(r2), "=r"(r3) : "r"(a) : "memory");
}
__device__ __forceinline__ void stsm4t(uint32_t a, uint32_t r0, uint32_t r1, uint32_t r2, uint32_t r3) {
  asm volatile("stmatrix.sync.aligned.m8n8.x4.trans.shared.b16 [%0], {%1,%2,%3,%4};" ::"r"(a), "r"(r0), "r"(r1), "r"(r2), "r"(r3) : "memory");
}
__device__ __forceinline__ void stsm2t(uint32_t a, uint32_t r0, uint32_t r1) {
  asm volatile("stmatrix.sync.aligned.m8n8.x2.trans.shared.b16 [%0], {%1,%2};" ::"r"(a), "r"(r0), "r"(r1) : "memory");
}
__device__ __forceinline__ uint32_t pack2(float lo, float hi) { uint32_t r; asm("cvt.rn.bf16x2.f32 %0, %1, %2;" : "=r"(r) : "f"(hi), "f"(lo)); return r; }
__device__ __forceinline__ float blo(uint32_t u) { return __uint_as_float(u << 16); }
__device__ __forceinline__ float bhi(uint32_t u) { return __uint_as_float(u & 0xffff0000u); }
__device__ __forceinline__ uint4 ldg128(const void* p) { uint4 v; asm volatile("ld.global.nc.L1::no_allocate.v4.u32 {%0,%1,%2,%3}, [%4];" : "=r"(v.x), "=r"(v.y), "=r"(v.z), "=r"(v.w) : "l"(p)); return v; }
__device__ __forceinline__ uint4 ldg128c(const void* p) { uint4 v; asm volatile("ld.global.nc.v4.u32 {%0,%1,%2,%3}, [%4];" : "=r"(v.x), "=r"(v.y), "=r"(v.z), "=r"(v.w) : "l"(p)); return v; }
__device__ __forceinline__ uint4 ldcg128(const void* p) { uint4 v; asm volatile("ld.global.cg.v4.u32 {%0,%1,%2,%3}, [%4];" : "=r"(v.x), "=r"(v.y), "=r"(v.z), "=r"(v.w) : "l"(p) : "memory"); return v; }
__device__ __forceinline__ float4 ldcg128f(const void* p) { float4 v; asm volatile("ld.global.cg.v4.f32 {%0,%1,%2,%3}, [%4];" : "=f"(v.x), "=f"(v.y), "=f"(v.z), "=f"(v.w) : "l"(p) : "memory"); return v; }
__device__ __forceinline__ float2 ldcg64f(const void* p) { float2 v; asm volatile("ld.global.cg.v2.f32 {%0,%1}, [%2];" : "=f"(v.x), "=f"(v.y) : "l"(p) : "memory"); return v; }
__device__ __forceinline__ float ldcg32f(const void* p) { float v; asm volatile("ld.global.cg.f32 %0, [%1];" : "=f"(v) : "l"(p) : "memory"); return v; }
__device__ __forceinline__ float gelu_half(float h) {
  float u = h * fmaf(h * h, 8.f * 0.044715f * 0.7978845608028654f, 2.f * 0.7978845608028654f), t;
  asm("tanh.approx.f32 %0, %1;" : "=f"(t) : "f"(u));
  return fmaf(h, t, h);
}
__device__ __forceinline__ void wgmma_rs_n128(float* d, uint32_t a0, uint32_t a1, uint32_t a2, uint32_t a3, uint64_t db) {
  asm volatile("wgmma.mma_async.sync.aligned.m64n128k16.f32.bf16.bf16 {%0, %1, %2, %3, %4, %5, %6, %7, %8, %9, %10, %11, %12, %13, %14, %15, %16, %17, %18, %19, %20, %21, %22, %23, %24, %25, %26, %27, %28, %29, %30, %31, %32, %33, %34, %35, %36, %37, %38, %39, %40, %41, %42, %43, %44, %45, %46, %47, %48, %49, %50, %51, %52, %53, %54, %55, %56, %57, %58, %59, %60, %61, %62, %63}, {%64, %65, %66, %67}, %68, 1, 1, 1, 0;"
    : "+f"(d[0]), "+f"(d[1]), "+f"(d[2]), "+f"(d[3]), "+f"(d[4]), "+f"(d[5]), "+f"(d[6]), "+f"(d[7]), "+f"(d[8]), "+f"(d[9]), "+f"(d[10]), "+f"(d[11]), "+f"(d[12]), "+f"(d[13]), "+f"(d[14]), "+f"(d[15]), "+f"(d[16]), "+f"(d[17]), "+f"(d[18]), "+f"(d[19]), "+f"(d[20]), "+f"(d[21]), "+f"(d[22]), "+f"(d[23]), "+f"(d[24]), "+f"(d[25]), "+f"(d[26]), "+f"(d[27]), "+f"(d[28]), "+f"(d[29]), "+f"(d[30]), "+f"(d[31]), "+f"(d[32]), "+f"(d[33]), "+f"(d[34]), "+f"(d[35]), "+f"(d[36]), "+f"(d[37]), "+f"(d[38]), "+f"(d[39]), "+f"(d[40]), "+f"(d[41]), "+f"(d[42]), "+f"(d[43]), "+f"(d[44]), "+f"(d[45]), "+f"(d[46]), "+f"(d[47]), "+f"(d[48]), "+f"(d[49]), "+f"(d[50]), "+f"(d[51]), "+f"(d[52]), "+f"(d[53]), "+f"(d[54]), "+f"(d[55]), "+f"(d[56]), "+f"(d[57]), "+f"(d[58]), "+f"(d[59]), "+f"(d[60]), "+f"(d[61]), "+f"(d[62]), "+f"(d[63])
    : "r"(a0), "r"(a1), "r"(a2), "r"(a3), "l"(db));
}
__device__ __forceinline__ void wgmma_rs_n96(float* d, uint32_t a0, uint32_t a1, uint32_t a2, uint32_t a3, uint64_t db) {
  asm volatile("wgmma.mma_async.sync.aligned.m64n96k16.f32.bf16.bf16 {%0, %1, %2, %3, %4, %5, %6, %7, %8, %9, %10, %11, %12, %13, %14, %15, %16, %17, %18, %19, %20, %21, %22, %23, %24, %25, %26, %27, %28, %29, %30, %31, %32, %33, %34, %35, %36, %37, %38, %39, %40, %41, %42, %43, %44, %45, %46, %47}, {%48, %49, %50, %51}, %52, 1, 1, 1, 0;"
    : "+f"(d[0]), "+f"(d[1]), "+f"(d[2]), "+f"(d[3]), "+f"(d[4]), "+f"(d[5]), "+f"(d[6]), "+f"(d[7]), "+f"(d[8]), "+f"(d[9]), "+f"(d[10]), "+f"(d[11]), "+f"(d[12]), "+f"(d[13]), "+f"(d[14]), "+f"(d[15]), "+f"(d[16]), "+f"(d[17]), "+f"(d[18]), "+f"(d[19]), "+f"(d[20]), "+f"(d[21]), "+f"(d[22]), "+f"(d[23]), "+f"(d[24]), "+f"(d[25]), "+f"(d[26]), "+f"(d[27]), "+f"(d[28]), "+f"(d[29]), "+f"(d[30]), "+f"(d[31]), "+f"(d[32]), "+f"(d[33]), "+f"(d[34]), "+f"(d[35]), "+f"(d[36]), "+f"(d[37]), "+f"(d[38]), "+f"(d[39]), "+f"(d[40]), "+f"(d[41]), "+f"(d[42]), "+f"(d[43]), "+f"(d[44]), "+f"(d[45]), "+f"(d[46]), "+f"(d[47])
    : "r"(a0), "r"(a1), "r"(a2), "r"(a3), "l"(db));
}
__device__ __forceinline__ void wgmma_rs_n64(float* d, uint32_t a0, uint32_t a1, uint32_t a2, uint32_t a3, uint64_t db) {
  asm volatile("wgmma.mma_async.sync.aligned.m64n64k16.f32.bf16.bf16 {%0, %1, %2, %3, %4, %5, %6, %7, %8, %9, %10, %11, %12, %13, %14, %15, %16, %17, %18, %19, %20, %21, %22, %23, %24, %25, %26, %27, %28, %29, %30, %31}, {%32, %33, %34, %35}, %36, 1, 1, 1, 0;"
    : "+f"(d[0]), "+f"(d[1]), "+f"(d[2]), "+f"(d[3]), "+f"(d[4]), "+f"(d[5]), "+f"(d[6]), "+f"(d[7]), "+f"(d[8]), "+f"(d[9]), "+f"(d[10]), "+f"(d[11]), "+f"(d[12]), "+f"(d[13]), "+f"(d[14]), "+f"(d[15]), "+f"(d[16]), "+f"(d[17]), "+f"(d[18]), "+f"(d[19]), "+f"(d[20]), "+f"(d[21]), "+f"(d[22]), "+f"(d[23]), "+f"(d[24]), "+f"(d[25]), "+f"(d[26]), "+f"(d[27]), "+f"(d[28]), "+f"(d[29]), "+f"(d[30]), "+f"(d[31])
    : "r"(a0), "r"(a1), "r"(a2), "r"(a3), "l"(db));
}
__device__ __forceinline__ void wgmma_rs_n32(float* d, uint32_t a0, uint32_t a1, uint32_t a2, uint32_t a3, uint64_t db) {
  asm volatile("wgmma.mma_async.sync.aligned.m64n32k16.f32.bf16.bf16 {%0, %1, %2, %3, %4, %5, %6, %7, %8, %9, %10, %11, %12, %13, %14, %15}, {%16, %17, %18, %19}, %20, 1, 1, 1, 0;"
    : "+f"(d[0]), "+f"(d[1]), "+f"(d[2]), "+f"(d[3]), "+f"(d[4]), "+f"(d[5]), "+f"(d[6]), "+f"(d[7]), "+f"(d[8]), "+f"(d[9]), "+f"(d[10]), "+f"(d[11]), "+f"(d[12]), "+f"(d[13]), "+f"(d[14]), "+f"(d[15])
    : "r"(a0), "r"(a1), "r"(a2), "r"(a3), "l"(db));
}
__device__ __forceinline__ void wgmma_ss_n80_t10(float* d, uint64_t da, uint64_t db) {
  asm volatile("wgmma.mma_async.sync.aligned.m64n80k16.f32.bf16.bf16 {%0, %1, %2, %3, %4, %5, %6, %7, %8, %9, %10, %11, %12, %13, %14, %15, %16, %17, %18, %19, %20, %21, %22, %23, %24, %25, %26, %27, %28, %29, %30, %31, %32, %33, %34, %35, %36, %37, %38, %39}, %40, %41, 1, 1, 1, 1, 0;"
    : "+f"(d[0]), "+f"(d[1]), "+f"(d[2]), "+f"(d[3]), "+f"(d[4]), "+f"(d[5]), "+f"(d[6]), "+f"(d[7]), "+f"(d[8]), "+f"(d[9]), "+f"(d[10]), "+f"(d[11]), "+f"(d[12]), "+f"(d[13]), "+f"(d[14]), "+f"(d[15]), "+f"(d[16]), "+f"(d[17]), "+f"(d[18]), "+f"(d[19]), "+f"(d[20]), "+f"(d[21]), "+f"(d[22]), "+f"(d[23]), "+f"(d[24]), "+f"(d[25]), "+f"(d[26]), "+f"(d[27]), "+f"(d[28]), "+f"(d[29]), "+f"(d[30]), "+f"(d[31]), "+f"(d[32]), "+f"(d[33]), "+f"(d[34]), "+f"(d[35]), "+f"(d[36]), "+f"(d[37]), "+f"(d[38]), "+f"(d[39])
    : "l"(da), "l"(db));
}
__device__ __forceinline__ void wgmma_ss_n152_t10(float* d, uint64_t da, uint64_t db) {
  asm volatile("wgmma.mma_async.sync.aligned.m64n152k16.f32.bf16.bf16 {%0, %1, %2, %3, %4, %5, %6, %7, %8, %9, %10, %11, %12, %13, %14, %15, %16, %17, %18, %19, %20, %21, %22, %23, %24, %25, %26, %27, %28, %29, %30, %31, %32, %33, %34, %35, %36, %37, %38, %39, %40, %41, %42, %43, %44, %45, %46, %47, %48, %49, %50, %51, %52, %53, %54, %55, %56, %57, %58, %59, %60, %61, %62, %63, %64, %65, %66, %67, %68, %69, %70, %71, %72, %73, %74, %75}, %76, %77, 1, 1, 1, 1, 0;"
    : "+f"(d[0]), "+f"(d[1]), "+f"(d[2]), "+f"(d[3]), "+f"(d[4]), "+f"(d[5]), "+f"(d[6]), "+f"(d[7]), "+f"(d[8]), "+f"(d[9]), "+f"(d[10]), "+f"(d[11]), "+f"(d[12]), "+f"(d[13]), "+f"(d[14]), "+f"(d[15]), "+f"(d[16]), "+f"(d[17]), "+f"(d[18]), "+f"(d[19]), "+f"(d[20]), "+f"(d[21]), "+f"(d[22]), "+f"(d[23]), "+f"(d[24]), "+f"(d[25]), "+f"(d[26]), "+f"(d[27]), "+f"(d[28]), "+f"(d[29]), "+f"(d[30]), "+f"(d[31]), "+f"(d[32]), "+f"(d[33]), "+f"(d[34]), "+f"(d[35]), "+f"(d[36]), "+f"(d[37]), "+f"(d[38]), "+f"(d[39]), "+f"(d[40]), "+f"(d[41]), "+f"(d[42]), "+f"(d[43]), "+f"(d[44]), "+f"(d[45]), "+f"(d[46]), "+f"(d[47]), "+f"(d[48]), "+f"(d[49]), "+f"(d[50]), "+f"(d[51]), "+f"(d[52]), "+f"(d[53]), "+f"(d[54]), "+f"(d[55]), "+f"(d[56]), "+f"(d[57]), "+f"(d[58]), "+f"(d[59]), "+f"(d[60]), "+f"(d[61]), "+f"(d[62]), "+f"(d[63]), "+f"(d[64]), "+f"(d[65]), "+f"(d[66]), "+f"(d[67]), "+f"(d[68]), "+f"(d[69]), "+f"(d[70]), "+f"(d[71]), "+f"(d[72]), "+f"(d[73]), "+f"(d[74]), "+f"(d[75])
    : "l"(da), "l"(db));
}

template <int KAP> __device__ __forceinline__ void conv_mma(float* acc, const uint32_t* a, uint64_t db) {
  if (KAP == 0) wgmma_rs_n128(acc, a[0], a[1], a[2], a[3], db);
  if (KAP == 1) wgmma_rs_n96(acc + 16, a[0], a[1], a[2], a[3], db);
  if (KAP == 2) wgmma_rs_n64(acc + 32, a[0], a[1], a[2], a[3], db);
  if (KAP == 3) wgmma_rs_n32(acc + 48, a[0], a[1], a[2], a[3], db);
}
template <int ST> __device__ __forceinline__ void conv_load(uint32_t (&a)[16], uint32_t pa, uint32_t zero) {
  constexpr int U = 512 * (ST / 2) + 64 * (ST % 2);
  uint32_t p[9];
#pragma unroll
  for (int i = 0; i < 9; i++) p[i] = lds32(pa + (U + 8 * i - 8) * 4);
#pragma unroll
  for (int r = 0; r < 4; r++) {
    a[4 * r + 0] = p[2 * r + 1];
    a[4 * r + 1] = p[2 * r + 2];
    a[4 * r + 2] = r == 0 ? p[0] : (p[2 * r] ^ zero);
    a[4 * r + 3] = p[2 * r + 1] ^ zero;
  }
}
template <int ST> __device__ __forceinline__ void conv_stage(float* acc, uint32_t (&a)[16], uint64_t db0) {
#pragma unroll
  for (int i = 0; i < 16; i++) asm volatile("" : "+r"(a[i])::"memory");
  wg_fence();
#pragma unroll
  for (int r = 0; r < 4; r++) conv_mma<ST / 2>(acc, a + 4 * r, db0 - (uint64_t)(4 * (ST % 2) + r));
  wg_commit();
}
template <int LO> __device__ __forceinline__ void conv_trans(float* acc, float zf) {
#pragma unroll
  for (int i = LO; i < 64; i++) acc[i] += zf;
}
__device__ __forceinline__ void conv_channel(uint32_t sb, int slot, int wg, int ch, uint32_t zero, float dcoef, long long t_start) {
  const int tid = threadIdx.x & 127, w = tid >> 5, lane = tid & 31, g = lane >> 2, t = lane & 3;
  const uint32_t P = sb + OFF_P + slot * PBYTES, X = sb + OFF_XC + slot * XBYTES + 128;
  const uint32_t pa = P + 64 + (128 * w + g - 2 * t) * 4;
  const uint64_t db0 = mkdesc(X, XLBO, 128, 0);
  const float zf = __uint_as_float(zero);
  float acc[64];
#pragma unroll
  for (int i = 0; i < 64; i++) acc[i] = 0.f;
  uint32_t a0[16], a1[16];
  conv_load<0>(a0, pa, zero);
  mbar_wait(BAR(B_XC + slot), 0);
  if (slot > 0) mbar_wait(slot == 1 ? BAR(B_TA) : BAR(B_TE + slot - 2), 0);
  PROF0(8 + 4 * slot);
  conv_stage<0>(acc, a0, db0); conv_load<1>(a1, pa, zero);
  conv_stage<1>(acc, a1, db0); wg_wait<1>(); conv_load<2>(a0, pa, zero);
  if (tid == 0 && slot == 0) mbar_arrive(BAR(B_TA));
  wg_wait<0>(); conv_trans<16>(acc, zf);
  conv_stage<2>(acc, a0, db0); conv_load<3>(a1, pa, zero);
  conv_stage<3>(acc, a1, db0); wg_wait<1>(); conv_load<4>(a0, pa, zero); wg_wait<0>(); conv_trans<32>(acc, zf);
  conv_stage<4>(acc, a0, db0); conv_load<5>(a1, pa, zero);
  conv_stage<5>(acc, a1, db0); wg_wait<1>(); conv_load<6>(a0, pa, zero);
  wg_wait<0>(); conv_trans<48>(acc, zf);
  if (tid == 0) mbar_arrive(BAR(B_TE + slot));
  conv_stage<6>(acc, a0, db0); conv_load<7>(a1, pa, zero);
  conv_stage<7>(acc, a1, db0); wg_wait<0>();
  PROF0(9 + 4 * slot);
  const uint32_t R = sb + OFF_RED + wg * RBYTES + lane * 16;
  float y[16];
#pragma unroll
  for (int ww = 0; ww < 4; ww++) {
    if (w == ww) {
#pragma unroll
      for (int j = 0; j < 16 - ww; j++) {
        const int jo = j + ww, ow = jo >> 2, jj = jo & 3;
        if (ow == ww) { y[4 * jj] = acc[4 * j]; y[4 * jj + 1] = acc[4 * j + 1]; y[4 * jj + 2] = acc[4 * j + 2]; y[4 * jj + 3] = acc[4 * j + 3]; }
        else {
          const int sidx = ww < ow ? ww : ww - 1;
          const int idx = ow > 0 ? 6 + (ow - 1) * 12 + sidx * 4 + jj : (ww == 1 ? jj - 1 : (ww == 2 ? 3 + jj - 2 : 5));
          sts128f(R + idx * 512, acc[4 * j], acc[4 * j + 1], acc[4 * j + 2], acc[4 * j + 3]);
        }
      }
    }
  }
  bar_sync(1 + wg, 128);
  if (w == 0) {
#pragma unroll
    for (int idx = 0; idx < 6; idx++) {
      const int jj = idx < 3 ? idx + 1 : (idx < 5 ? idx - 1 : 3);
      float4 v = lds128f(R + idx * 512);
      y[4 * jj] += v.x; y[4 * jj + 1] += v.y; y[4 * jj + 2] += v.z; y[4 * jj + 3] += v.w;
    }
  } else {
    const uint32_t Rw = R + (6 + (w - 1) * 12) * 512;
#pragma unroll
    for (int idx = 0; idx < 12; idx++) {
      const int jj = idx & 3;
      float4 v = lds128f(Rw + idx * 512);
      y[4 * jj] += v.x; y[4 * jj + 1] += v.y; y[4 * jj + 2] += v.z; y[4 * jj + 3] += v.w;
    }
  }
#pragma unroll
  for (int h = 0; h < 2; h++) {
    const int blk = 32 * w + 16 * h + 8 * (lane >> 4) + (lane & 7), half = (lane >> 3) & 1;
    uint32_t k0, k1, k2, k3;
    ldsm4t(X + half * XLBO + blk * 16, k0, k1, k2, k3);
    const float* yy = y + 8 * h;
    stsm4t(P + blk * 32 + half * 16,
           pack2(fmaf(dcoef, blo(k0), yy[0]), fmaf(dcoef, bhi(k0), yy[1])), pack2(fmaf(dcoef, blo(k1), yy[2]), fmaf(dcoef, bhi(k1), yy[3])),
           pack2(fmaf(dcoef, blo(k2), yy[4]), fmaf(dcoef, bhi(k2), yy[5])), pack2(fmaf(dcoef, blo(k3), yy[6]), fmaf(dcoef, bhi(k3), yy[7])));
  }
  fence_async_smem();
  bar_sync(1 + wg, 128);
  if (tid == 0) { bulk_store(g_yT + (size_t)ch * S, P, 4096); bulk_commit(); }
  PROF0(10 + 4 * slot);
}
__device__ __forceinline__ void conv_build(uint32_t sb, int slot, const uint2 (&kr)[4], const uint32_t (&pv)[4]) {
  const int tid = threadIdx.x & 127, lane = tid & 31;
  const uint32_t P = sb + OFF_P + slot * PBYTES + 64;
#pragma unroll
  for (int i = 0; i < 4; i++) {
    uint32_t prev = __shfl_up_sync(0xffffffffu, kr[i].y, 1);
    if (lane == 0) prev = pv[i];
    sts128u(P + (tid + 128 * i) * 16, __byte_perm(kr[i].x, prev, 0x7610), __byte_perm(kr[i].x, 0, 0x1032), __byte_perm(kr[i].y, kr[i].x, 0x7610), __byte_perm(kr[i].y, 0, 0x1032));
  }
  if (tid < 4) sts128u(P - 64 + tid * 16, 0, 0, 0, 0);
  if (tid < 16) sts128u(sb + OFF_XC + slot * XBYTES + (tid >> 3) * XLBO + (tid & 7) * 16, 0, 0, 0, 0);
}
__device__ __forceinline__ void conv_fetch(const __nv_bfloat16* ssm, int ch, uint2 (&kr)[4], uint32_t (&pv)[4]) {
  const int tid = threadIdx.x & 127, lane = tid & 31;
  const char* p = (const char*)(ssm + (size_t)ch * S);
#pragma unroll
  for (int i = 0; i < 4; i++) {
    const int c = tid + 128 * i;
    asm volatile("ld.global.nc.v2.u32 {%0,%1}, [%2];" : "=r"(kr[i].x), "=r"(kr[i].y) : "l"(p + c * 8));
    pv[i] = 0;
    if (lane == 0 && c > 0) asm volatile("ld.global.nc.u32 %0, [%1];" : "=r"(pv[i]) : "l"(p + c * 8 - 4));
  }
}

struct Ring { int ws, wp, xs, xp; };

template <int NR, int NWG, bool SHIFTED>
__device__ __forceinline__ void gemm_loop(float* acc, uint32_t sb, int wg, int nch, const Ring& r, int hold) {
  const bool leader = (threadIdx.x & 127) == 0;
  int ws = r.ws + wg, wp = r.wp;
  if (ws >= NWB) { ws -= NWB; wp ^= 1; }
  int xs = r.xs, xp = r.xp;
  int pws = -1, pxs = -1;
  for (int c = 0; c < nch; c++) {
    const int half = NWG == 2 ? (c & 1) : 0;
    mbar_wait(BAR(B_FW + ws), wp);
    mbar_wait(BAR(B_FX + 2 * xs + half), xp);
    const uint64_t da = mkdesc(sb + OFF_W + ws * 8192, 0, 1024, 1);
    const uint32_t xa = sb + OFF_X + xs * XSLOT + half * 10240;
    uint64_t db = mkdesc(xa, 16, 1024, 1), db2 = db + 4;
    if (SHIFTED && (c == 2 || c == 7)) { db = mkdesc(xa, 16, 512, 2); db2 = db + 320; }
    wg_fence();
    if (NR == 80) {
      wgmma_ss_n80_t10(acc, da, db); wgmma_ss_n80_t10(acc, da + 128, db + 2);
      wgmma_ss_n80_t10(acc, da + 256, db2); wgmma_ss_n80_t10(acc, da + 384, db2 + 2);
    } else {
      wgmma_ss_n152_t10(acc, da, db); wgmma_ss_n152_t10(acc, da + 128, db + 2);
      wgmma_ss_n152_t10(acc, da + 256, db2); wgmma_ss_n152_t10(acc, da + 384, db2 + 2);
    }
    wg_commit();
    wg_wait<1>();
    if (leader) {
      if (pws >= 0) mbar_arrive(BAR(B_EW + pws));
      if (pxs >= 0) mbar_arrive_n(BAR(B_EX + pxs), (NWG == 2 && wg == 0) ? 2 : 1);
    }
    pws = ws; pxs = -1;
    ws += NWG; if (ws >= NWB) { ws -= NWB; wp ^= 1; }
    if (NWG == 3 || half == 1 || c == nch - 1) {
      if (c < nch - hold) pxs = xs;
      if (++xs == 4) { xs = 0; xp ^= 1; }
    }
  }
  wg_wait<0>();
  if (leader) {
    mbar_arrive(BAR(B_EW + pws));
    if (pxs >= 0) mbar_arrive_n(BAR(B_EX + pxs), (NWG == 2 && wg == 0) ? 2 : 1);
  }
}
__device__ __forceinline__ void ring_advance(Ring& r, int nw, int nx) {
  r.ws += nw; while (r.ws >= NWB) { r.ws -= NWB; r.wp ^= 1; }
  r.xs += nx; while (r.xs >= 4) { r.xs -= 4; r.xp ^= 1; }
}

struct WStream { int i, slot, par, n3; };
__device__ __forceinline__ void w_issue(WStream& s, const Params& p, uint32_t sb, int ft, int ft3) {
  const int e3 = 40 + s.n3, tot = e3 + 54;
  if (s.i >= tot) return;
  const CUtensorMap* tm; int f, k;
  if (s.i < 40) { const int j = s.i < 20 ? s.i : s.i - 20; tm = s.i < 20 ? &p.w1 : &p.w2; f = ft * 128 + (j & 1) * 64; k = (j >> 1) * 64; }
  else if (s.i < e3) { const int j = s.i - 40, c = j / 3; tm = &p.w3; f = ft3 * 192 + (j - 3 * c) * 64; k = c * 64; }
  else { const int j = s.i - e3; tm = &p.w4; f = ft * 128 + (j & 1) * 64; k = (j >> 1) * 64; }
  mbar_wait(BAR(B_EW + s.slot), s.par);
  const uint32_t fb = BAR(B_FW + s.slot);
  mbar_expect(fb, 8192);
  tma_load(sb + OFF_W + s.slot * 8192, tm, fb, f, k);
  s.i++;
  if (++s.slot == NWB) { s.slot = 0; s.par ^= 1; }
}
struct XStream { int slot, par; };
template <int PH> __device__ __forceinline__ void x_issue(XStream& x, const Params& p, uint32_t sb, int u, int r0) {
  mbar_wait(BAR(B_EX + x.slot), x.par);
  const uint32_t fb = BAR(B_FX + 2 * x.slot), dst = sb + OFF_X + x.slot * XSLOT;
  if (PH == 3) {
    mbar_expect(fb, 152 * 128);
    tma_load(dst, &p.x1l, fb, u * 64, r0);
    mbar_arrive(fb + 8);
  } else {
#pragma unroll
    for (int h = 0; h < 2; h++) {
      const int c = 2 * u + h;
      if (PH == 4 && c == 27) { mbar_arrive(fb + 8); continue; }
      mbar_expect(fb + 8 * h, 10240);
      if (PH == 1) tma_load(dst + h * 10240, &p.h, fb + 8 * h, c * 64, r0);
      if (PH == 4) tma_load(dst + h * 10240, &p.hl, fb + 8 * h, c * 64, r0);
      if (PH == 2) {
        if (c == 2 || c == 7) {
          const int d = c == 2 ? 1 : 2;
          tma_load(dst + h * 10240, &p.h1n, fb + 8 * h, c * 64, r0 - d);
          tma_load(dst + h * 10240 + 5120, &p.h1n, fb + 8 * h, c * 64 + 32, r0 + d);
        } else {
          const int d = c < 2 ? -1 : (c < 5 ? 1 : (c < 7 ? -2 : 2));
          tma_load(dst + h * 10240, &p.h1, fb + 8 * h, c * 64, r0 + d);
        }
      }
    }
  }
  if (++x.slot == 4) { x.slot = 0; x.par ^= 1; }
}
template <int PH> __device__ __forceinline__ void produce_phase(WStream& ws, XStream& xs, const Params& p, uint32_t sb, int ft, int ft3, int r0) {
  constexpr int NCH = PH == 4 ? 27 : 10, NWG = PH == 3 ? 3 : 2, NX = PH == 3 ? 10 : (PH == 4 ? 14 : 5);
#pragma unroll 1
  for (int u = 0; u < 4; u++) x_issue<PH>(xs, p, sb, u, r0);
#pragma unroll 1
  for (int e = 0; e < NCH; e++) {
#pragma unroll 1
    for (int i = 0; i < NWG; i++) w_issue(ws, p, sb, ft, ft3);
    const int u = PH == 3 ? e : (e >> 1);
    if ((PH == 3 || (e & 1)) && u + 4 < NX) x_issue<PH>(xs, p, sb, u + 4, r0);
  }
}

__device__ __forceinline__ uint32_t tile_addr(uint32_t st) {
  const int lane = threadIdx.x & 31, w = (threadIdx.x >> 5) & 3;
  return st + (8 * (lane >> 4) + (lane & 7)) * 128 + (((2 * w + ((lane >> 3) & 1)) ^ (lane & 7)) << 4);
}
template <int NJ> __device__ __forceinline__ void stage_tile(uint32_t st, const uint32_t* pk) {
  const uint32_t a = tile_addr(st);
#pragma unroll
  for (int j = 0; j + 1 < NJ; j += 2) stsm4t(a + j * 1024, pk[2 * j], pk[2 * j + 1], pk[2 * j + 2], pk[2 * j + 3]);
  if (NJ & 1) stsm2t(a + (NJ - 1) * 1024 - ((threadIdx.x & 31) >> 4) * 1024, pk[2 * NJ - 2], pk[2 * NJ - 1]);
}
__device__ __forceinline__ void half_row_stats(uint32_t tile, uint32_t dst, int n) {
  const int r = n >> 1, hf = n & 1;
  const uint32_t a = tile + hf * 10240 + r * 128;
  float s1 = 0.f, s2 = 0.f;
#pragma unroll
  for (int i = 0; i < 8; i++) {
    const float4 v = lds128f(a + (((i + n) & 7) << 4));
    const uint32_t u[4] = {__float_as_uint(v.x), __float_as_uint(v.y), __float_as_uint(v.z), __float_as_uint(v.w)};
#pragma unroll
    for (int m = 0; m < 4; m++) { const float x0 = blo(u[m]), x1 = bhi(u[m]); s1 += x0 + x1; s2 = fmaf(x0, x0, fmaf(x1, x1, s2)); }
  }
  s1 += __shfl_xor_sync(0xffffffffu, s1, 1); s2 += __shfl_xor_sync(0xffffffffu, s2, 1);
  if (hf == 0) sts64f(dst + r * 8, s1, s2);
}
__device__ __forceinline__ float2 gather_stats(int which, int row) {
  float s1 = 0.f, s2 = 0.f;
  if (row < S) {
#pragma unroll
    for (int i = 0; i < 5; i++) { const float2 v = ldcg64f(&g_st[which][i][row]); s1 += v.x; s2 += v.y; }
  }
  const float m = s1 * (1.f / D);
  return make_float2(m, fmaxf(s2 * (1.f / D) - m * m, 0.f));
}
__device__ __forceinline__ void store_tile_stats(uint32_t sb, int wg, const uint32_t* pk, const CUtensorMap* tm, int f0, int r0, int ft, int which,
                                                 unsigned* cdata, unsigned* cstat) {
  const int tid = threadIdx.x;
  stage_tile<10>(sb + OFF_ST + wg * 10240, pk);
  fence_async_smem();
  bar_sync(5, 256);
  if ((tid & 127) == 127) { tma_store(tm, sb + OFF_ST + wg * 10240, f0, r0); bulk_commit(); bulk_wait0(); red_cnt(cdata); }
  __syncwarp();
  if (tid < 160) {
    half_row_stats(sb + OFF_ST, sb + OFF_PS, tid);
    fence_async_smem();
    bar_sync(7, 160);
    if (tid == 0) { bulk_store(&g_st[which][ft][r0], sb + OFF_PS, 640); bulk_commit(); bulk_wait0(); red_cnt(cstat); }
  }
}

__global__ void __launch_bounds__(NTHR, 1) fused_kernel(const __grid_constant__ Params p, uint32_t zero) {
  extern __shared__ __align__(1024) char smem[];
  const uint32_t sb = s2u(smem);
  const int b = blockIdx.x, tid = threadIdx.x;
  const int warp = __shfl_sync(0xffffffffu, tid >> 5, 0), lane = tid & 31, wg = warp >> 2;
  const int ft = b % 5, rt = b / 5, ft3 = b % 9, rt3 = b / 9;
  const bool has3 = b < 126, hasC = b < 128;
  const int r0 = rt * 80, r3 = rt3 * 152;

  if (wg == 3) {
    asm volatile("setmaxnreg.dec.sync.aligned.u32 56;");
    const unsigned e1 = *(volatile unsigned*)&g_epoch + 1;
    if (warp == 12) {
      if (elect_one()) {
        for (int i = 0; i < NBAR; i++) mbar_init(BAR(i), ((i >= B_EX && i < B_EX + 4) || i == B_CD) ? 3 : (i == B_TD ? 2 : 1));
        asm volatile("fence.mbarrier_init.release.cluster;" ::: "memory");
        fence_async_smem();
        if (hasC) {
          { long long t0 = clock64(); while (clock64() - t0 < SSM_DELAY) { } }
          bulk_prefetch(p.ssm + (size_t)b * 5 * S, 5 * S * 2);
        }
      }
      __syncthreads();
      if (elect_one()) {
        PROFT(0);
        tma_store4(&p.kv, sb + OFF_KV, (b / 10) * 80, (b % 10) * 8, 0, 0);
        bulk_commit();
        mbar_expect(BAR(B_QT), 20480);
        tma_load(sb + OFF_QT, &p.q80, BAR(B_QT), ft * 128, r0);
        tma_load(sb + OFF_QT + 10240, &p.q80, BAR(B_QT), ft * 128 + 64, r0);
        bulk_wait0();
        red_cnt(CNT(C_BAR1));
        PROFT(1);
        WStream ws{0, 0, 1, has3 ? 30 : 0};
        XStream xs{0, 1};
        wait_cnt(CNT(C_BAR1), e1 * NCTA);
        PROFT(2);
        if (hasC) {
          for (int j = 0; j < 5; j++) {
            const uint32_t fb = BAR(B_XC + j), dst = sb + OFF_XC + j * XBYTES + 128;
            mbar_expect(fb, 4096);
            bulk_load(dst, g_kvT + (size_t)(b * 5 + j) * S, 2048, fb);
            bulk_load(dst + XLBO, g_kvT + (size_t)(b * 5 + j) * S + 1024, 2048, fb);
          }
          bulk_prefetch(p.w1p + (size_t)b * 3200, 6400);
          bulk_prefetch(p.w3p + (size_t)b * 8640, 17280);
          bulk_prefetch(p.w2p + (size_t)b * 3200, 6400);
          bulk_prefetch(p.w4p + (size_t)b * 8640, 17280);
        }
        if (b == 0) *(volatile unsigned*)&g_epoch = e1;
#pragma unroll 1
        for (int i = 0; i < WFREE; i++) w_issue(ws, p, sb, ft, ft3);
        if (hasC) mbar_wait(BAR(B_CD), 0);
        wait_cnt(CNT(C_BAR2), e1 * (128 * 3 + 74));
        PROFT(3);
        mbar_expect(BAR(B_YT), 20480);
        tma_load(sb + OFF_YT, &p.y80, BAR(B_YT), r0, ft * 128);
        mbar_wait(BAR(B_TD), 0);
#pragma unroll 1
        for (int i = WFREE; i < NWB; i++) w_issue(ws, p, sb, ft, ft3);
        wait_cnt(CNT(C_T + rt), e1 * 10);
        PROFT(4);
        produce_phase<1>(ws, xs, p, sb, ft, ft3, r0);
        wait_cnt3(CNT(C_G1 + max(rt - 1, 0)), CNT(C_G1 + rt), CNT(C_G1 + min(rt + 1, 25)), e1 * 10);
        PROFT(5);
        produce_phase<2>(ws, xs, p, sb, ft, ft3, r0);
        if (has3) {
          const int lo = r3 / 80, hi = min(25, (r3 + 151) / 80);
          wait_cnt3(CNT(C_G2 + lo), CNT(C_G2 + lo + 1), CNT(C_G2 + hi), e1 * 10);
          PROFT(6);
          produce_phase<3>(ws, xs, p, sb, ft, ft3, r3);
        }
        const int lo = r0 / 152, hi = min(13, (r0 + 79) / 152);
        wait_cnt3(CNT(C_G3 + lo), CNT(C_G3 + hi), CNT(C_G3 + hi), e1 * 27);
        PROFT(7);
        produce_phase<4>(ws, xs, p, sb, ft, ft3, r0);
      }
    } else if (warp == 13) {
      __syncthreads();
      mbar_wait(BAR(B_QT), 0);
#pragma unroll 1
      for (int i = 0; i < 5; i++) half_row_stats(sb + OFF_QT, sb + OFF_PQ, lane + 32 * i);
      fence_async_smem();
      __syncwarp();
      if (lane == 0) { bulk_store(&g_st[0][ft][r0], sb + OFF_PQ, 640); bulk_commit(); bulk_wait0(); red_cnt(CNT(C_SQ + rt)); wait_cnt(CNT(C_SQ + rt), e1 * 5); }
      __syncwarp();
#pragma unroll 1
      for (int r = lane; r < 80; r += 32) { const float2 s = gather_stats(0, r0 + r); sts64f(sb + OFF_RQ + r * 8, s.x, rsqrtf(s.y + EPS)); }
      __syncwarp();
      if (lane == 0) { mbar_arrive(BAR(B_QS)); PROFT(28); wait_cnt(CNT(C_SH + rt), e1 * 5); }
      __syncwarp();
#pragma unroll 1
      for (int r = lane; r < 80; r += 32) {
        const float2 s = gather_stats(1, r0 + r);
        const float r1 = rsqrtf(s.y + EPS), r2 = 0.5f * r1 * rsqrtf(s.y * r1 * r1 + EPS);
        sts128f(sb + OFF_RP + r * 16, r2, -s.x * r2, r1, -s.x * r1);
      }
      __syncwarp();
      if (lane == 0) { mbar_arrive(BAR(B_RP)); PROFT(29); }
      if (has3) {
        if (lane == 0) { const int lo = r3 / 80, hi = min(25, (r3 + 151) / 80); wait_cnt3(CNT(C_SX + lo), CNT(C_SX + lo + 1), CNT(C_SX + hi), e1 * 5); }
        __syncwarp();
#pragma unroll 1
        for (int r = lane; r < 152; r += 32) { const float2 s = gather_stats(2, r3 + r); const float rs = 0.5f * rsqrtf(s.y + EPS); sts64f(sb + OFF_RP3 + r * 8, rs, -s.x * rs); }
        __syncwarp();
        if (lane == 0) { mbar_arrive(BAR(B_RP3)); PROFT(30); }
      }
    } else {
      __syncthreads();
      if (b < 74) {
        mbar_wait(BAR(B_XC), 0);
        const int ld = b < 54 ? FF : D;
        const __nv_bfloat16* src = (b < 54 ? p.w3p + b * 32 : p.w1p + (b - 54) * 32) + (size_t)((warp - 14) * 8 + (lane >> 2)) * ld + (lane & 3) * 8;
        float s[8];
#pragma unroll
        for (int i = 0; i < 8; i++) s[i] = 0.f;
#pragma unroll 1
        for (int it = 0; it < 8; it++) {
          uint4 u[5];
#pragma unroll
          for (int i = 0; i < 5; i++) u[i] = ldg128(src + (size_t)(it * 5 + i) * 16 * ld);
#pragma unroll
          for (int i = 0; i < 5; i++) {
            s[0] += blo(u[i].x); s[1] += bhi(u[i].x); s[2] += blo(u[i].y); s[3] += bhi(u[i].y);
            s[4] += blo(u[i].z); s[5] += bhi(u[i].z); s[6] += blo(u[i].w); s[7] += bhi(u[i].w);
          }
        }
#pragma unroll
        for (int i = 0; i < 8; i++) {
#pragma unroll
          for (int o = 4; o < 32; o <<= 1) s[i] += __shfl_xor_sync(0xffffffffu, s[i], o);
        }
        const uint32_t R = sb + OFF_CS;
        if (lane < 4) { sts128f(R + (warp - 14) * 128 + lane * 32, s[0], s[1], s[2], s[3]); sts128f(R + (warp - 14) * 128 + lane * 32 + 16, s[4], s[5], s[6], s[7]); }
        bar_sync(8, 64);
        if (warp == 14) {
          sts32f(R + 256 + lane * 4, __uint_as_float(lds32(R + lane * 4)) + __uint_as_float(lds32(R + 128 + lane * 4)));
          fence_async_smem();
          __syncwarp();
          if (lane == 0) { bulk_store(&g_cs[b * 32], R + 256, 128); bulk_commit(); bulk_wait0(); red_cnt(CNT(C_BAR2)); PROFT(31); }
        }
      }
    }
    return;
  }

  asm volatile("setmaxnreg.inc.sync.aligned.u32 152;");
  const int g = lane >> 2, t = lane & 3, w4 = warp & 3, tid7 = tid & 127;
  if (tid < 320) {
    const int o = lane & 7, gi = lane >> 3, c0 = 64 * (b % 10) + 8 * o, rb = 160 * (b / 10) + 16 * warp + 4 * gi;
    if (rb < S) {
      uint4 kk[7], vv[4], sw[4];
#pragma unroll
      for (int i = 0; i < 7; i++) { kk[i] = make_uint4(0, 0, 0, 0); if (rb + i - 3 >= 0) kk[i] = ldg128c(p.k + (size_t)(rb + i - 3) * D + c0); }
#pragma unroll
      for (int i = 0; i < 4; i++) vv[i] = ldg128(p.v + (size_t)(rb + i) * D + c0);
#pragma unroll
      for (int i = 0; i < 4; i++) sw[i] = ldg128c(p.shk + (size_t)c0 * 4 + 8 * i);
      const uint32_t dst = sb + OFF_KV + (gi >> 1) * 1280 + o * 160 + warp * 16 + (gi & 1) * 8;
#pragma unroll
      for (int j = 0; j < 8; j++) {
        const uint32_t s01 = ((const uint32_t*)sw)[2 * j], s23 = ((const uint32_t*)sw)[2 * j + 1];
        const float w0 = blo(s01), w1 = bhi(s01), w2 = blo(s23), w3 = bhi(s23);
        float kf[7], ov[4];
#pragma unroll
        for (int i = 0; i < 7; i++) { const uint32_t u = ((const uint32_t*)&kk[i])[j >> 1]; kf[i] = (j & 1) ? bhi(u) : blo(u); }
#pragma unroll
        for (int i = 0; i < 4; i++) {
          const uint32_t u = ((const uint32_t*)&vv[i])[j >> 1];
          ov[i] = fmaf(w0, kf[i + 3], fmaf(w1, kf[i + 2], fmaf(w2, kf[i + 1], w3 * kf[i]))) * ((j & 1) ? bhi(u) : blo(u));
        }
        sts64u(dst + j * 2560, pack2(ov[0], ov[1]), pack2(ov[2], ov[3]));
      }
      fence_async_smem();
    }
  }
  uint2 ka[4], kb[4]; uint32_t pa[4], pb[4];
  const int c0 = b * 5 + wg;
  if (hasC) {
    conv_fetch(p.ssm, c0, ka, pa);
    if (wg < 2) conv_fetch(p.ssm, c0 + 3, kb, pb);
  }
  __syncthreads();
  if (hasC) {
    conv_build(sb, wg, ka, pa);
    if (wg < 2) conv_build(sb, wg + 3, kb, pb);
    fence_async_smem();
    bar_sync(1 + wg, 128);
    PROF0(34 + wg);
#pragma unroll 1
    for (int slot = wg; slot < 5; slot += 3) conv_channel(sb, slot, wg, b * 5 + slot, zero, __bfloat162float(p.ssd[b * 5 + slot]), TST);
    if (tid7 == 0) { bulk_wait0(); red_cnt(CNT(C_BAR2)); mbar_arrive(BAR(B_CD)); PROFT(37 + wg); }
  }

  Ring ring{0, 0, 0, 0};
  float res[40];
  const uint32_t stg = sb + OFF_ST + wg * 10240;
  const int f0 = ft * 128 + wg * 64;
  if (wg < 2) {
    uint32_t hp[20];
    {
      mbar_wait(BAR(B_QT), 0);
      const uint32_t qa = tile_addr(sb + OFF_QT + wg * 10240);
#pragma unroll
      for (int j = 0; j < 10; j += 2) ldsm4t(qa + j * 1024, hp[2 * j], hp[2 * j + 1], hp[2 * j + 2], hp[2 * j + 3]);
      mbar_wait(BAR(B_QS), 0);
#pragma unroll
      for (int j = 0; j < 10; j++) {
        const float4 st = lds128f(sb + OFF_RQ + (8 * j + 2 * t) * 8);
        res[4 * j] = (blo(hp[2 * j]) - st.x) * st.y; res[4 * j + 1] = (bhi(hp[2 * j]) - st.z) * st.w;
        res[4 * j + 2] = (blo(hp[2 * j + 1]) - st.x) * st.y; res[4 * j + 3] = (bhi(hp[2 * j + 1]) - st.z) * st.w;
      }
      const uint32_t ya = sb + OFF_YT + (64 * wg + 16 * w4 + (lane & 15)) * 160 + (lane >> 4) * 16;
      mbar_wait(BAR(B_YT), 0);
      PROF0(40);
#pragma unroll
      for (int j = 0; j < 10; j += 2) {
        uint32_t y[4];
        ldsm4(ya + j * 16, y[0], y[1], y[2], y[3]);
#pragma unroll
        for (int m = 0; m < 4; m++)
          hp[2 * j + m] = pack2(fmaf(res[4 * j + 2 * m], blo(y[m]), blo(hp[2 * j + m])), fmaf(res[4 * j + 2 * m + 1], bhi(y[m]), bhi(hp[2 * j + m])));
      }
      store_tile_stats(sb, wg, hp, &p.h, f0, r0, ft, 1, CNT(C_T + rt), CNT(C_SH + rt));
      if (tid7 == 0) mbar_arrive(BAR(B_TD));
      PROF0(41);
    }
#pragma unroll
    for (int i = 0; i < 40; i++) res[i] = 0.f;
    const float c10 = ldcg32f(&g_cs[FF + f0 + 16 * w4 + g]), c11 = ldcg32f(&g_cs[FF + f0 + 16 * w4 + g + 8]);
    gemm_loop<80, 2, false>(res, sb, wg, 10, ring, 0);
    PROF0(42 + wg);
    {
      uint32_t pk[20];
      mbar_wait(BAR(B_RP), 0);
#pragma unroll
      for (int j = 0; j < 10; j++) {
        const float2 ra = lds64f(sb + OFF_RP + (8 * j + 2 * t) * 16), rb = lds64f(sb + OFF_RP + (8 * j + 2 * t + 1) * 16);
        pk[2 * j] = pack2(gelu_half(fmaf(res[4 * j], ra.x, ra.y * c10)), gelu_half(fmaf(res[4 * j + 1], rb.x, rb.y * c10)));
        pk[2 * j + 1] = pack2(gelu_half(fmaf(res[4 * j + 2], ra.x, ra.y * c11)), gelu_half(fmaf(res[4 * j + 3], rb.x, rb.y * c11)));
      }
      PROF0(44);
      stage_tile<10>(stg, pk);
      fence_async_smem();
      bar_sync(1 + wg, 128);
      if (tid7 == 127) { tma_store(&p.h1, stg, f0, r0); bulk_commit(); bulk_wait0(); red_cnt(CNT(C_G1 + rt)); PROFT(45 + wg); }
      __syncwarp();
    }
    ring_advance(ring, 20, 5);
#pragma unroll
    for (int j = 0; j < 10; j++) {
      const float2 ra = lds64f(sb + OFF_RP + (8 * j + 2 * t) * 16 + 8), rb = lds64f(sb + OFF_RP + (8 * j + 2 * t + 1) * 16 + 8);
      res[4 * j] = fmaf(blo(hp[2 * j]), ra.x, ra.y); res[4 * j + 1] = fmaf(bhi(hp[2 * j]), rb.x, rb.y);
      res[4 * j + 2] = fmaf(blo(hp[2 * j + 1]), ra.x, ra.y); res[4 * j + 3] = fmaf(bhi(hp[2 * j + 1]), rb.x, rb.y);
    }
    gemm_loop<80, 2, true>(res, sb, wg, 10, ring, 0);
    PROF0(47 + wg);
    if (has3) bar_arrive(6, 384);
    {
      uint32_t pk[20];
#pragma unroll
      for (int i = 0; i < 20; i++) pk[i] = pack2(res[2 * i], res[2 * i + 1]);
      store_tile_stats(sb, wg, pk, &p.x1s, f0, r0, ft, 2, CNT(C_G2 + rt), CNT(C_SX + rt));
#pragma unroll
      for (int i = 0; i < 20; i++) { res[2 * i] = blo(pk[i]) + blo(hp[i]); res[2 * i + 1] = bhi(pk[i]) + bhi(hp[i]); }
      PROF0(49 + wg);
    }
    ring_advance(ring, 20, 5);
  } else {
    ring_advance(ring, 40, 10);
    if (has3) bar_sync(6, 384);
  }
  if (has3) {
    float acc[76];
#pragma unroll
    for (int i = 0; i < 76; i++) acc[i] = 0.f;
    const int f3 = ft3 * 192 + wg * 64;
    const float cs0 = ldcg32f(&g_cs[f3 + 16 * w4 + g]), cs1 = ldcg32f(&g_cs[f3 + 16 * w4 + g + 8]);
    gemm_loop<152, 3, false>(acc, sb, wg, 10, ring, 3);
    PROF0(51 + wg);
    mbar_wait(BAR(B_RP3), 0);
    const int hs = (ring.xs + 7 + wg) & 3;
    uint32_t pk[38];
#pragma unroll
    for (int j = 0; j < 19; j++) {
      const float4 rp = lds128f(sb + OFF_RP3 + (8 * j + 2 * t) * 8);
      pk[2 * j] = pack2(gelu_half(fmaf(acc[4 * j], rp.x, rp.y * cs0)), gelu_half(fmaf(acc[4 * j + 1], rp.z, rp.w * cs0)));
      pk[2 * j + 1] = pack2(gelu_half(fmaf(acc[4 * j + 2], rp.x, rp.y * cs1)), gelu_half(fmaf(acc[4 * j + 3], rp.z, rp.w * cs1)));
    }
    bar_sync(9, 384);
    stage_tile<19>(sb + OFF_X + hs * XSLOT, pk);
    fence_async_smem();
    bar_sync(1 + wg, 128);
    PROF0(54 + wg);
    if (tid7 == 127) {
      tma_store(&p.hs, sb + OFF_X + hs * XSLOT, f3, r3); bulk_commit();
      bulk_wait0();
      red_cnt(CNT(C_G3 + rt3));
      mbar_arrive_n(BAR(B_EX + hs), 3);
      PROFT(57 + wg);
    }
    __syncwarp();
    ring_advance(ring, 30, 10);
  }
  if (wg < 2) {
    gemm_loop<80, 2, false>(res, sb, wg, 27, ring, 0);
    PROF0(60);
    uint32_t pk[20];
#pragma unroll
    for (int i = 0; i < 20; i++) pk[i] = pack2(res[2 * i], res[2 * i + 1]);
    stage_tile<10>(stg, pk);
    fence_async_smem();
    bar_sync(1 + wg, 128);
    if (tid7 == 0) { tma_store(&p.out, stg, f0, r0); bulk_commit(); bulk_wait0(); PROFT(61 + wg); }
  }
}

typedef CUresult (*EncFn)(CUtensorMap*, CUtensorMapDataType, cuuint32_t, void*, const cuuint64_t*, const cuuint64_t*, const cuuint32_t*,
                          const cuuint32_t*, CUtensorMapInterleave, CUtensorMapSwizzle, CUtensorMapL2promotion, CUtensorMapFloatOOBfill);
void make_map(EncFn enc, CUtensorMap* tm, const void* ptr, int cols, int rows, int bc, int br, CUtensorMapSwizzle sw) {
  cuuint64_t gd[2] = {(cuuint64_t)cols, (cuuint64_t)rows}, gs[1] = {(cuuint64_t)cols * 2};
  cuuint32_t bd[2] = {(cuuint32_t)bc, (cuuint32_t)br}, es[2] = {1, 1};
  enc(tm, CU_TENSOR_MAP_DATA_TYPE_BFLOAT16, 2, const_cast<void*>(ptr), gd, gs, bd, es, CU_TENSOR_MAP_INTERLEAVE_NONE, sw,
      CU_TENSOR_MAP_L2_PROMOTION_L2_128B, CU_TENSOR_MAP_FLOAT_OOB_FILL_NONE);
}
template <class T> void* sym_addr(T& s) { void* a = nullptr; cudaGetSymbolAddress(&a, s); return a; }

}

extern "C" void kernel_launch(void* const* d_in, const int* in_sizes, int n_in, void* d_out, int out_size) {
  (void)in_sizes; (void)n_in; (void)out_size;
  void* fn = nullptr; cudaDriverEntryPointQueryResult qr;
  cudaGetDriverEntryPoint("cuTensorMapEncodeTiled", &fn, cudaEnableDefault, &qr);
  EncFn enc = (EncFn)fn;
  Params p;
  typedef const __nv_bfloat16* BP;
  p.q = (BP)d_in[0]; p.k = (BP)d_in[1]; p.v = (BP)d_in[2]; p.shk = (BP)d_in[3]; p.ssm = (BP)d_in[4]; p.ssd = (BP)d_in[5];
  p.w1p = (BP)d_in[7]; p.w2p = (BP)d_in[8]; p.w3p = (BP)d_in[9]; p.w4p = (BP)d_in[10];
  const CUtensorMapSwizzle S128 = CU_TENSOR_MAP_SWIZZLE_128B, S64 = CU_TENSOR_MAP_SWIZZLE_64B, S0 = CU_TENSOR_MAP_SWIZZLE_NONE;
  make_map(enc, &p.w1, p.w1p, D, D, 64, 64, S128);
  make_map(enc, &p.w2, p.w2p, D, D, 64, 64, S128);
  make_map(enc, &p.w3, p.w3p, FF, D, 64, 64, S128);
  make_map(enc, &p.w4, p.w4p, D, FF, 64, 64, S128);
  {
    cuuint64_t gd[4] = {1024, 80, 2, 8}, gs[3] = {32768, 2048, 4096};
    cuuint32_t bd[4] = {80, 8, 2, 8}, es[4] = {1, 1, 1, 1};
    CUresult r = enc(&p.kv, CU_TENSOR_MAP_DATA_TYPE_BFLOAT16, 4, sym_addr(g_kvT), gd, gs, bd, es, CU_TENSOR_MAP_INTERLEAVE_NONE, S0,
        CU_TENSOR_MAP_L2_PROMOTION_NONE, CU_TENSOR_MAP_FLOAT_OOB_FILL_NONE);
    (void)r;
  }
  make_map(enc, &p.q80, p.q, D, S, 64, 80, S128);
  make_map(enc, &p.y80, sym_addr(g_yT), S, D, 80, 128, S0);
  make_map(enc, &p.h, sym_addr(g_h), D, S, 64, 80, S128);
  make_map(enc, &p.h1, sym_addr(g_h1), D, S, 64, 80, S128);
  make_map(enc, &p.h1n, sym_addr(g_h1), D, S, 32, 80, S64);
  make_map(enc, &p.x1s, sym_addr(g_x1), D, S, 64, 80, S128);
  make_map(enc, &p.x1l, sym_addr(g_x1), D, S, 64, 152, S128);
  make_map(enc, &p.hs, sym_addr(g_hid), FF, S, 64, 152, S128);
  make_map(enc, &p.hl, sym_addr(g_hid), FF, S, 64, 80, S128);
  make_map(enc, &p.out, d_out, D, S, 64, 80, S128);
  cudaFuncSetAttribute(fused_kernel, cudaFuncAttributeMaxDynamicSharedMemorySize, SMEM_BYTES);
  fused_kernel<<<NCTA, NTHR, SMEM_BYTES, cudaStreamPerThread>>>(p, 0u);
}
```

```cpp
#include <cuda_runtime.h>
#include <cuda.h>
#include <cuda_bf16.h>
#include <stdint.h>

namespace {

constexpr int S = 2048, D = 640, FF = 1728;
constexpr int NCTA = 130, NTHR = 512;
constexpr float EPS = 1e-5f;
#define RED16 1
#define GSYNC 8
#define MAP3 1
#define WEARLY 4
#define WEARLY4 4
#define DRY 1
#define PFMODE 3
#define EXPT 0
#define GATE 2
#define WLATE 1
#define LAG2 3
#define LAG3 3

constexpr int NWU = 6, WU = 16384;
constexpr int OFF_W = 0;
constexpr int OFF_X = NWU * WU;
constexpr int XS = 20480;
constexpr int OFF_ST = OFF_X + 5 * XS;
constexpr int OFF_MISC = OFF_ST + 20480;
constexpr int OFF_BAR = OFF_MISC;
constexpr int OFF_RP = OFF_MISC + 640;
constexpr int OFF_RP3 = OFF_RP + 1280;
constexpr int OFF_RQ = OFF_RP3 + 1280;
constexpr int OFF_PS = OFF_RQ + 640;
constexpr int OFF_PQ = OFF_PS + 1280;
constexpr int OFF_CS = OFF_PQ + 1280;
constexpr int OFF_C1 = OFF_CS + 640;
constexpr int OFF_EP = OFF_C1 + 512;
constexpr int SMEM_BYTES = 232448;
static_assert(OFF_EP + 16 <= SMEM_BYTES, "smem");
constexpr int OFF_KV = 0;
constexpr int OFF_QT = 71680;
constexpr int OFF_YT = OFF_X + 4 * XS;
constexpr int CB = 92160;
constexpr int PBYTES = 8448, XBYTES = 4352, XLBO = 2176, RBYTES = RED16 ? 10752 : 21504;
constexpr int OFF_P = CB, OFF_XC = CB + 5 * PBYTES, OFF_RED = OFF_XC + 5 * XBYTES;
static_assert(OFF_RED + 3 * RBYTES <= OFF_MISC, "conv overlay");
constexpr int WFREE = 4;
constexpr int B_FW = 0, B_EW = 6, B_FX = 12, B_EX = 17, B_XC = 22, B_CD = 27, B_QT = 28, B_QS = 29, B_YT = 30, B_QD = 31, B_RP = 32, B_RP3 = 33,
              B_TA = 34  , B_K1 = 36, B_K2 = 37, B_K3 = 38, B_SF = 39  , B_DEP = 42  , B_PF = 52, B_SG = 53  , B_XI = 56, B_E4 = 57  , NBAR = 63;
#define BAR(i) (sb + OFF_BAR + 8 * (i))
constexpr uint32_t SB = 1024;

struct alignas(64) Params {
  CUtensorMap w1, w2, w3, w4, kv, q80, y80, h, h1, x1s, out, h2, h1n, x1l, hs, hl2;
  const __nv_bfloat16 *q, *k, *v, *shk, *ssm, *ssd, *w1p, *w2p, *w3p, *w4p;
};

constexpr int SP = S + 128;
__device__ __align__(1024) __nv_bfloat16 g_kvT[D * S];
__device__ __align__(1024) __nv_bfloat16 g_yB[26 * D * 80];
__device__ __align__(1024) __nv_bfloat16 g_h[S * D];
__device__ __align__(1024) __nv_bfloat16 g_h1[S * D];
__device__ __align__(1024) __nv_bfloat16 g_x1[S * D];
__device__ __align__(1024) __nv_bfloat16 g_hid[S * FF];
__device__ __align__(128) float2 g_st[3][10][SP];
__device__ __align__(128) float g_cs[FF + D];
__device__ __align__(128) unsigned g_cnt[320 * 32];
__device__ unsigned g_epoch;
constexpr int C_BAR1 = 0, C_BAR2 = 16, C_T = 32, C_G1 = 58  , C_G2 = 110  , C_G3 = 162  , C_SQ = 204, C_SH = 230,
              C_SX = 256, C_CS = 282;
#define CNT(i) (&g_cnt[(i) * 32])
#define PROFT(i) do { } while (0)
#define PROF0(i) do { } while (0)
#define TST 0

__device__ __forceinline__ uint32_t s2u(const void* p) { return (uint32_t)__cvta_generic_to_shared(p); }
__device__ __forceinline__ void mbar_init(uint32_t b, int c) { asm volatile("mbarrier.init.shared::cta.b64 [%0], %1;" ::"r"(b), "r"(c) : "memory"); }
__device__ __forceinline__ void mbar_expect(uint32_t b, int bytes) { asm volatile("mbarrier.arrive.expect_tx.shared::cta.b64 _, [%0], %1;" ::"r"(b), "r"(bytes) : "memory"); }
__device__ __forceinline__ void mbar_arrive(uint32_t b) { asm volatile("mbarrier.arrive.shared::cta.b64 _, [%0];" ::"r"(b) : "memory"); }
__device__ __forceinline__ void mbar_arrive_n(uint32_t b, int n) { asm volatile("mbarrier.arrive.shared::cta.b64 _, [%0], %1;" ::"r"(b), "r"(n) : "memory"); }
__device__ __forceinline__ bool mbar_try(uint32_t b, uint32_t parity) {
  uint32_t ok;
  asm volatile("{\n.reg .pred p;\nmbarrier.try_wait.parity.shared::cta.b64 p, [%1], %2;\nselp.u32 %0, 1, 0, p;\n}" : "=r"(ok) : "r"(b), "r"(parity) : "memory");
  return ok;
}
__device__ __forceinline__ void mbar_wait(uint32_t b, uint32_t parity) {
  if (mbar_try(b, parity)) return;
  int it = 0;
  while (!mbar_try(b, parity)) { if (++it > (1 << 22)) __trap(); }
}
__device__ __forceinline__ void wait_cnt(const unsigned* p, unsigned target) {
  unsigned v; int it = 0;
  while (true) {
    asm volatile("ld.acquire.gpu.global.u32 %0, [%1];" : "=r"(v) : "l"(p) : "memory");
    if ((int)(v - target) >= 0) break;
    if (++it > (1 << 22)) __trap();
  }
}
__device__ __forceinline__ void red_release(unsigned* p) { asm volatile("red.release.gpu.global.add.u32 [%0], 1;" ::"l"(p) : "memory"); }
__device__ __forceinline__ void fence_async_all() { asm volatile("fence.proxy.async;" ::: "memory"); }
__device__ __forceinline__ void fence_async_smem() { asm volatile("fence.proxy.async.shared::cta;" ::: "memory"); }
__device__ __forceinline__ void bar_sync(int id, int n) { asm volatile("bar.sync %0, %1;" ::"r"(id), "r"(n) : "memory"); }
__device__ __forceinline__ bool elect_one() {
  uint32_t e; asm volatile("{\n.reg .pred p;\nelect.sync _|p, 0xffffffff;\nselp.u32 %0, 1, 0, p;\n}" : "=r"(e)); return e;
}
__device__ __forceinline__ void tma_load(uint32_t dst, const CUtensorMap* tm, uint32_t bar, int c0, int c1) {
  asm volatile("cp.async.bulk.tensor.2d.shared::cluster.global.mbarrier::complete_tx::bytes [%0], [%1, {%3, %4}], [%2];"
               ::"r"(dst), "l"(tm), "r"(bar), "r"(c0), "r"(c1) : "memory");
}
__device__ __forceinline__ void tma_load3(uint32_t dst, const CUtensorMap* tm, uint32_t bar, int c0, int c1, int c2) {
  asm volatile("cp.async.bulk.tensor.3d.shared::cluster.global.mbarrier::complete_tx::bytes [%0], [%1, {%3, %4, %5}], [%2];"
               ::"r"(dst), "l"(tm), "r"(bar), "r"(c0), "r"(c1), "r"(c2) : "memory");
}
__device__ __forceinline__ void tma_store(const CUtensorMap* tm, uint32_t src, int c0, int c1) {
  asm volatile("cp.async.bulk.tensor.2d.global.shared::cta.bulk_group [%0, {%2, %3}], [%1];" ::"l"(tm), "r"(src), "r"(c0), "r"(c1) : "memory");
}
__device__ __forceinline__ void bulk_load(uint32_t dst, const void* src, int bytes, uint32_t bar) {
  asm volatile("cp.async.bulk.shared::cluster.global.mbarrier::complete_tx::bytes [%0], [%1], %2, [%3];" ::"r"(dst), "l"(src), "r"(bytes), "r"(bar) : "memory");
}
__device__ __forceinline__ void bulk_store(void* dst, uint32_t src, int bytes) {
  asm volatile("cp.async.bulk.global.shared::cta.bulk_group [%0], [%1], %2;" ::"l"(dst), "r"(src), "r"(bytes) : "memory");
}
__device__ __forceinline__ void bulk_prefetch(const void* src, int bytes) { asm volatile("cp.async.bulk.prefetch.L2.global [%0], %1;" ::"l"(src), "r"(bytes) : "memory"); }
__device__ __forceinline__ void prefetch_l2(const void* p) { asm volatile("prefetch.global.L2 [%0];" ::"l"(p)); }
__device__ __forceinline__ void bulk_commit() { asm volatile("cp.async.bulk.commit_group;" ::: "memory"); }
__device__ __forceinline__ void bulk_wait0() { asm volatile("cp.async.bulk.wait_group 0;" ::: "memory"); }
__device__ __forceinline__ void bulk_wait0_read() { asm volatile("cp.async.bulk.wait_group.read 0;" ::: "memory"); }
__device__ __forceinline__ void wg_fence() { asm volatile("wgmma.fence.sync.aligned;" ::: "memory"); }
__device__ __forceinline__ void wg_commit() { asm volatile("wgmma.commit_group.sync.aligned;" ::: "memory"); }
template <int N> __device__ __forceinline__ void wg_wait() { asm volatile("wgmma.wait_group.sync.aligned %0;" ::"n"(N) : "memory"); }
__device__ __forceinline__ uint64_t mkdesc(uint32_t addr, uint32_t lbo, uint32_t sbo, uint32_t swz) {
  return (uint64_t)((addr & 0x3FFFF) >> 4) | ((uint64_t)(lbo >> 4) << 16) | ((uint64_t)(sbo >> 4) << 32) | ((uint64_t)swz << 62);
}
__device__ __forceinline__ uint32_t lds32(uint32_t a) { uint32_t v; asm volatile("ld.shared.b32 %0, [%1];" : "=r"(v) : "r"(a) : "memory"); return v; }
__device__ __forceinline__ float4 lds128f(uint32_t a) { float4 v; asm volatile("ld.shared.v4.f32 {%0,%1,%2,%3}, [%4];" : "=f"(v.x), "=f"(v.y), "=f"(v.z), "=f"(v.w) : "r"(a) : "memory"); return v; }
__device__ __forceinline__ float2 lds64f(uint32_t a) { float2 v; asm volatile("ld.shared.v2.f32 {%0,%1}, [%2];" : "=f"(v.x), "=f"(v.y) : "r"(a) : "memory"); return v; }
__device__ __forceinline__ void sts128f(uint32_t a, float x, float y, float z, float w) { asm volatile("st.shared.v4.f32 [%0], {%1,%2,%3,%4};" ::"r"(a), "f"(x), "f"(y), "f"(z), "f"(w) : "memory"); }
__device__ __forceinline__ void sts128u(uint32_t a, uint32_t x, uint32_t y, uint32_t z, uint32_t w) { asm volatile("st.shared.v4.b32 [%0], {%1,%2,%3,%4};" ::"r"(a), "r"(x), "r"(y), "r"(z), "r"(w) : "memory"); }
__device__ __forceinline__ void sts64f(uint32_t a, float x, float y) { asm volatile("st.shared.v2.f32 [%0], {%1,%2};" ::"r"(a), "f"(x), "f"(y) : "memory"); }
__device__ __forceinline__ void ldsm4t(uint32_t a, uint32_t& r0, uint32_t& r1, uint32_t& r2, uint32_t& r3) {
  asm volatile("ldmatrix.sync.aligned.m8n8.x4.trans.shared.b16 {%0,%1,%2,%3}, [%4];" : "=r"(r0), "=r"(r1), "=r"(r2), "=r"(r3) : "r"(a) : "memory");
}
__device__ __forceinline__ void stsm4t(uint32_t a, uint32_t r0, uint32_t r1, uint32_t r2, uint32_t r3) {
  asm volatile("stmatrix.sync.aligned.m8n8.x4.trans.shared.b16 [%0], {%1,%2,%3,%4};" ::"r"(a), "r"(r0), "r"(r1), "r"(r2), "r"(r3) : "memory");
}
__device__ __forceinline__ void stsm2t(uint32_t a, uint32_t r0, uint32_t r1) {
  asm volatile("stmatrix.sync.aligned.m8n8.x2.trans.shared.b16 [%0], {%1,%2};" ::"r"(a), "r"(r0), "r"(r1) : "memory");
}
__device__ __forceinline__ uint32_t pack2(float lo, float hi) { uint32_t r; asm("cvt.rn.bf16x2.f32 %0, %1, %2;" : "=r"(r) : "f"(hi), "f"(lo)); return r; }
__device__ __forceinline__ float blo(uint32_t u) { return __uint_as_float(u << 16); }
__device__ __forceinline__ float bhi(uint32_t u) { return __uint_as_float(u & 0xffff0000u); }
__device__ __forceinline__ uint4 ldg128(const void* p) { uint4 v; asm volatile("ld.global.nc.L1::no_allocate.v4.u32 {%0,%1,%2,%3}, [%4];" : "=r"(v.x), "=r"(v.y), "=r"(v.z), "=r"(v.w) : "l"(p)); return v; }
__device__ __forceinline__ uint4 ldg128c(const void* p) { uint4 v; asm volatile("ld.global.nc.v4.u32 {%0,%1,%2,%3}, [%4];" : "=r"(v.x), "=r"(v.y), "=r"(v.z), "=r"(v.w) : "l"(p)); return v; }
__device__ __forceinline__ uint4 ldcg128(const void* p) { uint4 v; asm volatile("ld.global.cg.v4.u32 {%0,%1,%2,%3}, [%4];" : "=r"(v.x), "=r"(v.y), "=r"(v.z), "=r"(v.w) : "l"(p) : "memory"); return v; }
__device__ __forceinline__ float4 ldcg128f(const void* p) { float4 v; asm volatile("ld.global.cg.v4.f32 {%0,%1,%2,%3}, [%4];" : "=f"(v.x), "=f"(v.y), "=f"(v.z), "=f"(v.w) : "l"(p) : "memory"); return v; }
__device__ __forceinline__ float2 ldcg64f(const void* p) { float2 v; asm volatile("ld.global.cg.v2.f32 {%0,%1}, [%2];" : "=f"(v.x), "=f"(v.y) : "l"(p) : "memory"); return v; }
__device__ __forceinline__ float ldcg32f(const void* p) { float v; asm volatile("ld.global.cg.f32 %0, [%1];" : "=f"(v) : "l"(p) : "memory"); return v; }
__device__ __forceinline__ float gelu_half(float h) {
  float u = h * fmaf(h * h, 8.f * 0.044715f * 0.7978845608028654f, 2.f * 0.7978845608028654f), t;
  asm("tanh.approx.f32 %0, %1;" : "=f"(t) : "f"(u));
  return fmaf(h, t, h);
}
__device__ __forceinline__ void wgmma_rs_n64(float* d, uint32_t a0, uint32_t a1, uint32_t a2, uint32_t a3, uint64_t db) {
  asm volatile("wgmma.mma_async.sync.aligned.m64n64k16.f32.bf16.bf16 {%0, %1, %2, %3, %4, %5, %6, %7, %8, %9, %10, %11, %12, %13, %14, %15, %16, %17, %18, %19, %20, %21, %22, %23, %24, %25, %26, %27, %28, %29, %30, %31}, {%32, %33, %34, %35}, %36, 1, 1, 1, 0;"
    : "+f"(d[0]), "+f"(d[1]), "+f"(d[2]), "+f"(d[3]), "+f"(d[4]), "+f"(d[5]), "+f"(d[6]), "+f"(d[7]), "+f"(d[8]), "+f"(d[9]), "+f"(d[10]), "+f"(d[11]), "+f"(d[12]), "+f"(d[13]), "+f"(d[14]), "+f"(d[15]), "+f"(d[16]), "+f"(d[17]), "+f"(d[18]), "+f"(d[19]), "+f"(d[20]), "+f"(d[21]), "+f"(d[22]), "+f"(d[23]), "+f"(d[24]), "+f"(d[25]), "+f"(d[26]), "+f"(d[27]), "+f"(d[28]), "+f"(d[29]), "+f"(d[30]), "+f"(d[31])
    : "r"(a0), "r"(a1), "r"(a2), "r"(a3), "l"(db));
}
__device__ __forceinline__ void wgmma_rs_n32(float* d, uint32_t a0, uint32_t a1, uint32_t a2, uint32_t a3, uint64_t db) {
  asm volatile("wgmma.mma_async.sync.aligned.m64n32k16.f32.bf16.bf16 {%0, %1, %2, %3, %4, %5, %6, %7, %8, %9, %10, %11, %12, %13, %14, %15}, {%16, %17, %18, %19}, %20, 1, 1, 1, 0;"
    : "+f"(d[0]), "+f"(d[1]), "+f"(d[2]), "+f"(d[3]), "+f"(d[4]), "+f"(d[5]), "+f"(d[6]), "+f"(d[7]), "+f"(d[8]), "+f"(d[9]), "+f"(d[10]), "+f"(d[11]), "+f"(d[12]), "+f"(d[13]), "+f"(d[14]), "+f"(d[15])
    : "r"(a0), "r"(a1), "r"(a2), "r"(a3), "l"(db));
}
__device__ __forceinline__ void wgmma_ss_n80_t10(float* d, uint64_t da, uint64_t db) {
  asm volatile("wgmma.mma_async.sync.aligned.m64n80k16.f32.bf16.bf16 {%0, %1, %2, %3, %4, %5, %6, %7, %8, %9, %10, %11, %12, %13, %14, %15, %16, %17, %18, %19, %20, %21, %22, %23, %24, %25, %26, %27, %28, %29, %30, %31, %32, %33, %34, %35, %36, %37, %38, %39}, %40, %41, 1, 1, 1, 1, 0;"
    : "+f"(d[0]), "+f"(d[1]), "+f"(d[2]), "+f"(d[3]), "+f"(d[4]), "+f"(d[5]), "+f"(d[6]), "+f"(d[7]), "+f"(d[8]), "+f"(d[9]), "+f"(d[10]), "+f"(d[11]), "+f"(d[12]), "+f"(d[13]), "+f"(d[14]), "+f"(d[15]), "+f"(d[16]), "+f"(d[17]), "+f"(d[18]), "+f"(d[19]), "+f"(d[20]), "+f"(d[21]), "+f"(d[22]), "+f"(d[23]), "+f"(d[24]), "+f"(d[25]), "+f"(d[26]), "+f"(d[27]), "+f"(d[28]), "+f"(d[29]), "+f"(d[30]), "+f"(d[31]), "+f"(d[32]), "+f"(d[33]), "+f"(d[34]), "+f"(d[35]), "+f"(d[36]), "+f"(d[37]), "+f"(d[38]), "+f"(d[39])
    : "l"(da), "l"(db));
}
__device__ __forceinline__ void wgmma_ss_n152_t10(float* d, uint64_t da, uint64_t db) {
  asm volatile("wgmma.mma_async.sync.aligned.m64n152k16.f32.bf16.bf16 {%0, %1, %2, %3, %4, %5, %6, %7, %8, %9, %10, %11, %12, %13, %14, %15, %16, %17, %18, %19, %20, %21, %22, %23, %24, %25, %26, %27, %28, %29, %30, %31, %32, %33, %34, %35, %36, %37, %38, %39, %40, %41, %42, %43, %44, %45, %46, %47, %48, %49, %50, %51, %52, %53, %54, %55, %56, %57, %58, %59, %60, %61, %62, %63, %64, %65, %66, %67, %68, %69, %70, %71, %72, %73, %74, %75}, %76, %77, 1, 1, 1, 1, 0;"
    : "+f"(d[0]), "+f"(d[1]), "+f"(d[2]), "+f"(d[3]), "+f"(d[4]), "+f"(d[5]), "+f"(d[6]), "+f"(d[7]), "+f"(d[8]), "+f"(d[9]), "+f"(d[10]), "+f"(d[11]), "+f"(d[12]), "+f"(d[13]), "+f"(d[14]), "+f"(d[15]), "+f"(d[16]), "+f"(d[17]), "+f"(d[18]), "+f"(d[19]), "+f"(d[20]), "+f"(d[21]), "+f"(d[22]), "+f"(d[23]), "+f"(d[24]), "+f"(d[25]), "+f"(d[26]), "+f"(d[27]), "+f"(d[28]), "+f"(d[29]), "+f"(d[30]), "+f"(d[31]), "+f"(d[32]), "+f"(d[33]), "+f"(d[34]), "+f"(d[35]), "+f"(d[36]), "+f"(d[37]), "+f"(d[38]), "+f"(d[39]), "+f"(d[40]), "+f"(d[41]), "+f"(d[42]), "+f"(d[43]), "+f"(d[44]), "+f"(d[45]), "+f"(d[46]), "+f"(d[47]), "+f"(d[48]), "+f"(d[49]), "+f"(d[50]), "+f"(d[51]), "+f"(d[52]), "+f"(d[53]), "+f"(d[54]), "+f"(d[55]), "+f"(d[56]), "+f"(d[57]), "+f"(d[58]), "+f"(d[59]), "+f"(d[60]), "+f"(d[61]), "+f"(d[62]), "+f"(d[63]), "+f"(d[64]), "+f"(d[65]), "+f"(d[66]), "+f"(d[67]), "+f"(d[68]), "+f"(d[69]), "+f"(d[70]), "+f"(d[71]), "+f"(d[72]), "+f"(d[73]), "+f"(d[74]), "+f"(d[75])
    : "l"(da), "l"(db));
}

template <int ST> __device__ __forceinline__ void conv_load(uint32_t (&a)[16], uint32_t pa, uint32_t zero) {
  constexpr int U = 512 * (ST / 2) + 64 * (ST % 2);
  uint32_t p[9];
#pragma unroll
  for (int i = 0; i < 9; i++) p[i] = lds32(pa + (U + 8 * i - 8) * 4);
#pragma unroll
  for (int r = 0; r < 4; r++) {
    a[4 * r + 0] = p[2 * r + 1];
    a[4 * r + 1] = p[2 * r + 2];
    a[4 * r + 2] = r == 0 ? p[0] : (p[2 * r] ^ zero);
    a[4 * r + 3] = p[2 * r + 1] ^ zero;
  }
}
__device__ __forceinline__ void conv_fa(uint32_t (&a)[16]) {
#pragma unroll
  for (int i = 0; i < 16; i++) asm volatile("" : "+r"(a[i])::"memory");
  wg_fence();
}
template <int N> __device__ __forceinline__ void conv_g(float* acc, const uint32_t (&a)[16], uint64_t db) {
#pragma unroll
  for (int r = 0; r < 4; r++) {
    if (N == 64) wgmma_rs_n64(acc, a[4 * r], a[4 * r + 1], a[4 * r + 2], a[4 * r + 3], db - (uint64_t)r);
    else wgmma_rs_n32(acc, a[4 * r], a[4 * r + 1], a[4 * r + 2], a[4 * r + 3], db - (uint64_t)r);
  }
}
__device__ __forceinline__ void red_add(float* y, uint32_t a) {
  const float2 v = lds64f(a);
  const uint32_t u0 = __float_as_uint(v.x), u1 = __float_as_uint(v.y);
  y[0] += blo(u0); y[1] += bhi(u0); y[2] += blo(u1); y[3] += bhi(u1);
}
__device__ __forceinline__ void conv_channel(uint32_t sb, int slot, int wg, int ch, uint32_t zero, float dcoef, const CUtensorMap* ym, long long t_start) {
  const int tid = threadIdx.x & 127, w = __shfl_sync(0xffffffffu, tid >> 5, 0), lane = tid & 31, g = lane >> 2, t = lane & 3;
  const uint32_t P = sb + OFF_P + slot * PBYTES, X = sb + OFF_XC + slot * XBYTES + 128;
  const uint32_t pa = P + 64 + (128 * w + g - 2 * t) * 4;
  const uint64_t db0 = mkdesc(X, XLBO, 128, 0);
  const float zf = __uint_as_float(zero);
  float acc[64];
#pragma unroll
  for (int i = 0; i < 64; i++) acc[i] = 0.f;
  uint32_t a0[16], a1[16];
  conv_load<6>(a0, pa, zero);
  mbar_wait_u(BAR(B_XC + slot), 0);
  if (slot == 1 || slot == 2) mbar_wait_u(BAR(B_TA + slot - 1), 0);
  PROF0(8 + 4 * slot);
  conv_fa(a0); conv_g<32>(acc + 48, a0, db0); wg_commit(); conv_load<7>(a1, pa, zero);
  conv_fa(a1); conv_g<32>(acc + 48, a1, db0 - 4); wg_commit(); wg_wait<1>(); conv_load<0>(a0, pa, zero);
  conv_fa(a0); conv_g<64>(acc, a0, db0); wg_commit(); wg_wait<1>();
  conv_load<1>(a1, pa, zero);
#pragma unroll
  for (int i = 48; i < 64; i++) acc[i] += zf;
  wg_fence(); conv_g<64>(acc + 32, a0, db0 + 64); wg_commit();
  conv_fa(a1); conv_g<64>(acc, a1, db0 - 4); conv_g<64>(acc + 32, a1, db0 + 60); wg_commit(); wg_wait<1>();
  mbar_arrive_if(BAR(B_TA), tid == 0 && slot == 0);
  conv_load<2>(a0, pa, zero);
  conv_fa(a0); conv_g<64>(acc + 32, a0, db0 + 32); wg_commit(); wg_wait<1>();
  conv_load<3>(a1, pa, zero);
#pragma unroll
  for (int i = 16; i < 32; i++) acc[i] += zf;
  wg_fence(); conv_g<32>(acc + 16, a0, db0); wg_commit();
  conv_fa(a1); conv_g<64>(acc + 32, a1, db0 + 28); conv_g<32>(acc + 16, a1, db0 - 4); wg_commit(); wg_wait<1>();
  conv_load<4>(a0, pa, zero);
  mbar_arrive_if(BAR(B_TA + 1), tid == 0 && slot == 0);
  conv_fa(a0); conv_g<64>(acc + 32, a0, db0); wg_commit(); wg_wait<1>();
  conv_load<5>(a1, pa, zero);
  conv_fa(a1); conv_g<64>(acc + 32, a1, db0 - 4); wg_commit(); wg_wait<0>();
  PROF0(9 + 4 * slot);
  constexpr int RS = RED16 ? 256 : 512;
  const uint32_t R = sb + OFF_RED + wg * RBYTES + lane * (RS / 32);
  float y[16];
#pragma unroll
  for (int ww = 0; ww < 4; ww++) {
    if (w == ww) {
#pragma unroll
      for (int j = 0; j < 16 - ww; j++) {
        const int jo = j + ww, ow = jo >> 2, jj = jo & 3;
        if (ow == ww) { y[4 * jj] = acc[4 * j]; y[4 * jj + 1] = acc[4 * j + 1]; y[4 * jj + 2] = acc[4 * j + 2]; y[4 * jj + 3] = acc[4 * j + 3]; }
        else {
          const int sidx = ww < ow ? ww : ww - 1;
          const int idx = ow > 0 ? 6 + (ow - 1) * 12 + sidx * 4 + jj : (ww == 1 ? jj - 1 : (ww == 2 ? 3 + jj - 2 : 5));
          sts64u(R + idx * RS, pack2(acc[4 * j], acc[4 * j + 1]), pack2(acc[4 * j + 2], acc[4 * j + 3]));
        }
      }
    }
  }
  uint32_t kf[8];
#pragma unroll
  for (int h = 0; h < 2; h++)
    ldsm4t(X + ((lane >> 3) & 1) * XLBO + (32 * w + 16 * h + 8 * (lane >> 4) + (lane & 7)) * 16, kf[4 * h], kf[4 * h + 1], kf[4 * h + 2], kf[4 * h + 3]);
#pragma unroll
  for (int i = 0; i < 8; i++) { y[2 * i] = fmaf(dcoef, blo(kf[i]), y[2 * i]); y[2 * i + 1] = fmaf(dcoef, bhi(kf[i]), y[2 * i + 1]); }
  bar_sync(1 + wg, 128);
  if (w == 0) {
#pragma unroll
    for (int idx = 0; idx < 6; idx++) red_add(y + 4 * (idx < 3 ? idx + 1 : (idx < 5 ? idx - 1 : 3)), R + idx * RS);
  } else {
    const uint32_t Rw = R + (6 + (w - 1) * 12) * RS;
#pragma unroll
    for (int idx = 0; idx < 12; idx++) red_add(y + 4 * (idx & 3), Rw + idx * RS);
  }
#pragma unroll
  for (int h = 0; h < 2; h++) {
    const float* yy = y + 8 * h;
    stsm4t(P + (32 * w + 16 * h + 8 * (lane >> 4) + (lane & 7)) * 32 + ((lane >> 3) & 1) * 16,
           pack2(yy[0], yy[1]), pack2(yy[2], yy[3]), pack2(yy[4], yy[5]), pack2(yy[6], yy[7]));
  }
  fence_async_smem();
  bar_sync(1 + wg, 128);
  if (w == 0 && elect_one()) { tma_store3(ym, P, 0, ch, 0); bulk_commit(); }
  PROF0(10 + 4 * slot);
}
__device__ __forceinline__ void conv_build(uint32_t sb, int slot, const uint2 (&kr)[4], const uint32_t (&pv)[4]) {
  const int tid = threadIdx.x & 127, lane = tid & 31;
  const uint32_t P = sb + OFF_P + slot * PBYTES + 64;
#pragma unroll
  for (int i = 0; i < 4; i++) {
    uint32_t prev = __shfl_up_sync(0xffffffffu, kr[i].y, 1);
    if (lane == 0) prev = pv[i];
    sts128u(P + (tid + 128 * i) * 16, __byte_perm(kr[i].x, prev, 0x7610), __byte_perm(kr[i].x, 0, 0x1032), __byte_perm(kr[i].y, kr[i].x, 0x7610), __byte_perm(kr[i].y, 0, 0x1032));
  }
  if (tid < 4) sts128u(P - 64 + tid * 16, 0, 0, 0, 0);
  if (tid < 16) sts128u(sb + OFF_XC + slot * XBYTES + (tid >> 3) * XLBO + (tid & 7) * 16, 0, 0, 0, 0);
}
__device__ __forceinline__ void conv_fetch(const __nv_bfloat16* ssm, int ch, uint2 (&kr)[4], uint32_t (&pv)[4]) {
  const int tid = threadIdx.x & 127, lane = tid & 31;
  const char* p = (const char*)(ssm + (size_t)ch * S);
#pragma unroll
  for (int i = 0; i < 4; i++) {
    const int c = tid + 128 * i;
    asm volatile("ld.global.nc.v2.u32 {%0,%1}, [%2];" : "=r"(kr[i].x), "=r"(kr[i].y) : "l"(p + c * 8));
    pv[i] = 0;
    if (lane == 0 && c > 0) asm volatile("ld.global.nc.u32 %0, [%1];" : "=r"(pv[i]) : "l"(p + c * 8 - 4));
  }
}

struct Cur {
  uint32_t slot, par;
  template <int N> __device__ __forceinline__ void adv(uint32_t n) { slot += n; if (slot >= N) { slot -= N; par ^= 1; } }
};

__host__ __device__ constexpr int unit_key(int nwg, int w, int u) { return nwg == 2 ? u + w * LAG2 : 2 * u + (w ? LAG3 : 0); }
__host__ __device__ constexpr int unit_pos(int nwg, int w, int u) {
  int n = 0;
  for (int w2 = 0; w2 < nwg; w2++)
    for (int u2 = 0; u2 < 5; u2++) n += unit_key(nwg, w2, u2) < unit_key(nwg, w, u) || (unit_key(nwg, w2, u2) == unit_key(nwg, w, u) && w2 < w);
  return n;
}
__host__ __device__ constexpr uint32_t unit_slots(int nwg, int w, int base) {
  uint32_t m = 0;
  for (int u = 0; u < 5; u++) { const int q = base + unit_pos(nwg, w, u); m |= (uint32_t)(q % NWU | ((q / NWU) & 1) << 3) << (4 * u); }
  return m;
}
__host__ __device__ constexpr uint64_t unit_order(int nwg) {
  uint64_t m = 0;
  for (int w = 0; w < nwg; w++)
    for (int u = 0; u < 5; u++) m |= (uint64_t)(w * 5 + u) << (4 * unit_pos(nwg, w, u));
  return m;
}
constexpr uint64_t D128 = ((uint64_t)1 << 62) | ((uint64_t)64 << 32), D64 = ((uint64_t)2 << 62) | ((uint64_t)32 << 32);
constexpr uint64_t DA0 = D128 | ((SB + OFF_W) >> 4), DB0 = D128 | (1 << 16) | ((SB + OFF_X) >> 4), DBS = D64 | (1 << 16) | ((SB + OFF_X) >> 4);
template <int NR> __device__ __forceinline__ void mma4(float* acc, uint64_t da, uint64_t db, uint64_t db2) {
  if (NR == 80) {
    wgmma_ss_n80_t10(acc, da, db); wgmma_ss_n80_t10(acc, da + 128, db + 2);
    wgmma_ss_n80_t10(acc, da + 256, db2); wgmma_ss_n80_t10(acc, da + 384, db2 + 2);
  } else {
    wgmma_ss_n152_t10(acc, da, db); wgmma_ss_n152_t10(acc, da + 128, db + 2);
    wgmma_ss_n152_t10(acc, da + 256, db2); wgmma_ss_n152_t10(acc, da + 384, db2 + 2);
  }
}
template <int PH> __device__ __forceinline__ void mma_g12(float* acc, int wg, bool leader, long long t_start, int pb) {
  constexpr uint32_t sb = SB;
  constexpr uint32_t s0 = unit_slots(2, 0, 10 * (PH - 1)), s1 = unit_slots(2, 1, 10 * (PH - 1));
  const uint32_t sl = wg == 0 ? s0 : s1, xcnt = wg == 0 ? 2 : 1;
  if (wg == 1) mbar_wait_u(BAR(B_K1 + PH - 1), 0);
#pragma unroll
  for (int u = 0; u < 5; u++) {
    const uint32_t ws = (sl >> (4 * u)) & 7;
    mbar_wait2(BAR(B_FW) + 8 * ws, (sl >> (4 * u + 3)) & 1, BAR(B_FX + u), PH - 1);
    const uint64_t da = DA0 + ws * (WU / 16);
    constexpr uint64_t xo = XS / 16;
    wg_fence();
    if (PH == 2 && u == 1) mma4<80>(acc, da, DBS + u * xo, DBS + u * xo + 320); else mma4<80>(acc, da, DB0 + u * xo, DB0 + u * xo + 4);
    if (PH == 2 && u == 3) mma4<80>(acc, da + 512, DBS + u * xo + 640, DBS + u * xo + 960); else mma4<80>(acc, da + 512, DB0 + u * xo + 640, DB0 + u * xo + 644);
    wg_commit();
    if (u == LAG2 - 1) mbar_arrive_if(BAR(B_K1 + PH - 1), leader && wg == 0);
    if (u > 0) {
      wg_wait<1>();
      mbar_arrive_if(BAR(B_EW) + 8 * ((sl >> (4 * u - 4)) & 7), leader);
      mbar_arrive_n_if(BAR(B_EX + u - 1), xcnt, leader);
    }
  }
  wg_wait<0>();
  mbar_arrive_if(BAR(B_EW) + 8 * ((sl >> 16) & 7), leader);
  mbar_arrive_n_if(BAR(B_EX + 4), xcnt, leader);
}
__device__ __forceinline__ void mma_g3(float* acc, int wg, bool leader, long long t_start, int pb) {
  constexpr uint32_t sb = SB;
  uint32_t sl = wg == 0 ? unit_slots(3, 0, 20) : (wg == 1 ? unit_slots(3, 1, 20) : unit_slots(3, 2, 20));
  if (wg > 0) mbar_wait_u(BAR(B_K3), 0);
  uint32_t xs = 0, xp = 0, pw = 0, px = 0;
#pragma unroll 1
  for (int u = 0; u < 5; u++) {
    const uint32_t ws = sl & 7;
    const uint64_t da = DA0 + ws * (WU / 16);
#pragma unroll
    for (int h = 0; h < 2; h++) {
      if (h == 0) mbar_wait2(BAR(B_FW) + 8 * ws, (sl >> 3) & 1, BAR(B_FX) + 8 * xs, xp); else mbar_wait1(BAR(B_FX) + 8 * xs, xp);
      const uint64_t db = DB0 + xs * (XS / 16);
      wg_fence();
      mma4<152>(acc, da + 512 * h, db, db + 4);
      wg_commit();
      if (h == ((LAG3 - 1) & 1)) mbar_arrive_if(BAR(B_K3), leader && wg == 0 && u == (LAG3 - 1) / 2);
      wg_wait<1>();
      if (h == 0) mbar_arrive_if(BAR(B_EW) + 8 * pw, leader && u > 0);
      mbar_arrive_if(BAR(B_EX) + 8 * px, leader && (h == 1 || u > 0));
      px = xs;
      if (++xs == 5) { xs = 0; xp = 1; }
    }
    pw = ws; sl >>= 4;
  }
  wg_wait<0>();
  mbar_arrive_if(BAR(B_EW) + 8 * pw, leader);
  mbar_arrive_if(BAR(B_EX) + 8 * px, leader);
}
__device__ __forceinline__ void mma_g4(float* acc, int wg, uint32_t pos, bool leader, long long t_start, int pb) {
  constexpr uint32_t sb = SB;
  const uint32_t xcnt = wg == 0 ? 2 : 1;
  const uint64_t da0 = DA0 + wg * 512;
  Cur w{pos % NWU, (pos / NWU) & 1}, x{0, 0};
  uint32_t pw = 0, px = 0;
#pragma unroll 1
  for (int c = 0; c < 27; c++) {
    mbar_wait2(BAR(B_FW) + 8 * w.slot, w.par, BAR(B_FX) + 8 * x.slot, x.par);
    const uint64_t db = DB0 + x.slot * (XS / 16) + (c & 1) * 640;
    wg_fence();
    mma4<80>(acc, da0 + w.slot * (WU / 16), db, db + 4);
    wg_commit();
    wg_wait<1>();
    mbar_arrive_if(BAR(B_E4) + 8 * pw, leader && c > 0);
    mbar_arrive_n_if(BAR(B_EX) + 8 * px, xcnt, leader && c > 0 && !(c & 1));
    pw = w.slot; px = x.slot;
    w.adv<NWU>(1); x.adv<5>(c & 1);
  }
  wg_wait<0>();
}

__device__ __forceinline__ void w_unit(Cur& s, const CUtensorMap* tm, int f, int k) {
  constexpr uint32_t sb = SB;
  mbar_wait(BAR(B_EW) + 8 * s.slot, s.par ^ 1);
  mbar_expect(BAR(B_FW) + 8 * s.slot, WU);
  tma_load(sb + OFF_W + s.slot * WU, tm, BAR(B_FW) + 8 * s.slot, f, k);
  s.adv<NWU>(1);
}

__device__ __forceinline__ uint32_t tile_addr(uint32_t st) {
  const int lane = threadIdx.x & 31, w = (threadIdx.x >> 5) & 3;
  return st + (8 * (lane >> 4) + (lane & 7)) * 128 + (((2 * w + ((lane >> 3) & 1)) ^ (lane & 7)) << 4);
}
template <int NJ> __device__ __forceinline__ void stage_tile(uint32_t st, const uint32_t* pk) {
  const uint32_t a = tile_addr(st);
#pragma unroll
  for (int j = 0; j + 1 < NJ; j += 2) stsm4t(a + j * 1024, pk[2 * j], pk[2 * j + 1], pk[2 * j + 2], pk[2 * j + 3]);
  if (NJ & 1) stsm2t(a + (NJ - 1) * 1024 - ((threadIdx.x & 31) >> 4) * 1024, pk[2 * NJ - 2], pk[2 * NJ - 1]);
}
__device__ __forceinline__ void row_stats(uint32_t tile, uint32_t dst, int r) {
  float s1 = 0.f, s2 = 0.f;
#pragma unroll 2
  for (int i = 0; i < 8; i++) {
    const float4 v = lds128f(tile + r * 128 + (((i + r) & 7) << 4));
    const uint32_t u[4] = {__float_as_uint(v.x), __float_as_uint(v.y), __float_as_uint(v.z), __float_as_uint(v.w)};
#pragma unroll
    for (int m = 0; m < 4; m++) { const float x0 = blo(u[m]), x1 = bhi(u[m]); s1 += x0 + x1; s2 = fmaf(x0, x0, fmaf(x1, x1, s2)); }
  }
  sts64f(dst + r * 8, s1, s2);
}
__device__ __forceinline__ float2 gather_stats(int which, int row) {
  float s1 = 0.f, s2 = 0.f;
#pragma unroll
  for (int i = 0; i < 10; i++) { const float2 v = ldcg64f(&g_st[which][i][row]); s1 += v.x; s2 += v.y; }
  const float m = s1 * (1.f / D);
  return make_float2(m, fmaxf(s2 * (1.f / D) - m * m, 0.f));
}
__global__ void __launch_bounds__(NTHR, 1) fused_kernel(const __grid_constant__ Params p, uint32_t zero) {
  extern __shared__ __align__(1024) char smem[];
  constexpr uint32_t sb = SB;
  if (s2u(smem) != SB) return;
  const int b = blockIdx.x, tid = threadIdx.x;
  const int warp = __shfl_sync(0xffffffffu, tid >> 5, 0), lane = tid & 31, wg = warp >> 2;
  const int ft = b % 5, rt = b / 5;
  const int pb3 = b < 90 ? b / 45 : 2, pr3 = b < 90 ? 5 : 4, ib3 = b - 45 * pb3;
  const int ft3 = (ib3 / (3 * pr3)) * 3 + ib3 % 3, rt3 = 5 * pb3 + (ib3 % (3 * pr3)) / 3;
  const bool has3 = b < 126, hasC = b < 128;
  const int r0 = rt * 80, r3 = rt3 * 152;

  if (tid < 320) {
    const int o = lane & 7, gi = lane >> 3, c0 = 64 * (b % 10) + 8 * o, rb = 160 * (b / 10) + 16 * warp + 4 * gi;
    if (rb < S) {
      uint4 kk[7], vv[4], sw[4];
#pragma unroll
      for (int i = 3; i < 7; i++) kk[i] = ldg128c(p.k + (size_t)(rb + i - 3) * D + c0);
#pragma unroll
      for (int i = 0; i < 4; i++) vv[i] = ldg128(p.v + (size_t)(rb + i) * D + c0);
#pragma unroll
      for (int i = 0; i < 3; i++) { kk[i] = make_uint4(0, 0, 0, 0); if (rb > 0) kk[i] = ldg128c(p.k + (size_t)(rb + i - 3) * D + c0); }
#pragma unroll
      for (int i = 0; i < 4; i++) sw[i] = ldg128c(p.shk + (size_t)c0 * 4 + 8 * i);
      const uint32_t dst = sb + OFF_KV + (gi >> 1) * 1280 + o * 160 + warp * 16 + (gi & 1) * 8;
#pragma unroll
      for (int j = 0; j < 8; j++) {
        const uint32_t s01 = ((const uint32_t*)sw)[2 * j], s23 = ((const uint32_t*)sw)[2 * j + 1];
        const float w0 = blo(s01), w1 = bhi(s01), w2 = blo(s23), w3 = bhi(s23);
        float kf[7], ov[4];
#pragma unroll
        for (int i = 0; i < 7; i++) { const uint32_t u = ((const uint32_t*)&kk[i])[j >> 1]; kf[i] = (j & 1) ? bhi(u) : blo(u); }
#pragma unroll
        for (int i = 0; i < 4; i++) {
          const uint32_t u = ((const uint32_t*)&vv[i])[j >> 1];
          ov[i] = fmaf(w0, kf[i + 3], fmaf(w1, kf[i + 2], fmaf(w2, kf[i + 1], w3 * kf[i]))) * ((j & 1) ? bhi(u) : blo(u));
        }
        sts64u(dst + j * 2560, pack2(ov[0], ov[1]), pack2(ov[2], ov[3]));
      }
      fence_async_smem();
    }
  } else if (warp == 12 && elect_one()) {
#pragma unroll
    for (int i = 0; i < NBAR; i++) mbar_init(BAR(i), ((i >= B_EX && i < B_EX + 5) || i == B_CD || i == B_QD) ? 3 : (i >= B_E4 ? 2 : 1));
    asm volatile("fence.mbarrier_init.release.cluster;" ::: "memory");
    fence_async_smem();
  }

  if (wg == 3) {
    const unsigned e1 = *(volatile unsigned*)&g_epoch + 1;
    if (tid == 511) sts32f(sb + OFF_EP, __uint_as_float(e1));
    __syncthreads();
    asm volatile("setmaxnreg.dec.sync.aligned.u32 56;");
    if (warp == 12) {
      if (elect_one()) {
        PROFT(0);
        tma_store4(&p.kv, sb + OFF_KV, (b / 10) * 80, (b % 10) * 8, 0, 0);
        bulk_commit();
        bulk_wait0();
        red_cnt(CNT(C_BAR1 + (b & 15)));
        PROFT(1);
        mbar_wait(BAR(B_DEP), 0);
        PROFT(2);
        if (hasC) {
#pragma unroll 1
          for (int j = 0; j < 5; j++) {
            const uint32_t fb = BAR(B_XC + j), dst = sb + OFF_XC + j * XBYTES + 128;
            mbar_expect(fb, 4096);
            bulk_load(dst, g_kvT + (size_t)(b * 5 + j) * S, 2048, fb);
            bulk_load(dst + XLBO, g_kvT + (size_t)(b * 5 + j) * S + 1024, 2048, fb);
          }
        }
        mbar_expect(BAR(B_QT), 20480);
        tma_load(sb + OFF_QT, &p.q80, BAR(B_QT), ft * 64, r0);
        tma_load(sb + OFF_QT + 10240, &p.q80, BAR(B_QT), ft * 64 + 320, r0);
        if (b == 0) *(volatile unsigned*)&g_epoch = e1;
        if (hasC) { mbar_wait(BAR(B_CD), 0); if (PFMODE == 3) mbar_wait(BAR(B_PF), 0); }
        mbar_expect(BAR(B_YT), 20480);
        mbar_wait(BAR(B_DEP + 1), 0);
        bulk_load(sb + OFF_YT, g_yB + ((size_t)rt * D + ft * 64) * 80, 10240, BAR(B_YT));
        bulk_load(sb + OFF_YT + 10240, g_yB + ((size_t)rt * D + ft * 64 + 320) * 80, 10240, BAR(B_YT));
        PROFT(3);
#pragma unroll
        for (int u = 0; u < 5; u++) mbar_expect(BAR(B_FX + u), XS);
        mbar_wait(BAR(B_DEP + 2), 0);
#pragma unroll
        for (int u = 0; u < 5; u++) tma_load3(sb + OFF_X + u * XS, &p.h2, BAR(B_FX + u), 0, r0, 2 * u);
        PROFT(4);
#pragma unroll
        for (int u = 0; u < 5; u++) { mbar_wait(BAR(B_EX + u), 0); mbar_expect(BAR(B_FX + u), XS); }
#pragma unroll
        for (int c = 0; c < 10; c++) {
          if (c == 0 || c == 5) { mbar_wait(BAR(B_DEP + 3 + c / 5), 0); PROFT(c == 0 ? 5 : 27); }
          const int d = c < 5 ? 1 : 2;
          const uint32_t dst = sb + OFF_X + c * 10240;
          if (c == 2 || c == 7) {
            tma_load(dst, &p.h1n, BAR(B_FX + c / 2), c * 64, r0 - d);
            tma_load(dst + 5120, &p.h1n, BAR(B_FX + c / 2), c * 64 + 32, r0 + d);
          } else {
            tma_load(dst, &p.h1, BAR(B_FX + c / 2), c * 64, (c < 2 || c == 5 || c == 6) ? r0 - d : r0 + d);
          }
        }
        if (has3) {
#pragma unroll 1
          for (int c = 0; c < 10; c++) {
            const int cls = c >= 5, j = c - 5 * cls;
            mbar_wait(BAR(B_EX) + 8 * j, cls ^ 1);
            mbar_expect(BAR(B_FX) + 8 * j, 152 * 128);
            if (j == 0) { mbar_wait(BAR(B_DEP + 5) + 8 * cls, 0); PROFT(c == 0 ? 6 : 11); }
            tma_load(sb + OFF_X + j * XS, &p.x1l, BAR(B_FX) + 8 * j, c * 64, r3);
          }
        }
        Cur xs{0, 0};
#pragma unroll 1
        for (int u = 0; u < 14; u++) {
          mbar_wait(BAR(B_EX) + 8 * xs.slot, xs.par ^ 1);
          mbar_expect(BAR(B_FX) + 8 * xs.slot, XS);
          if (u == 0 || u == 4 || u == 9) { mbar_wait(BAR(B_DEP + 7) + (u == 0 ? 0 : (u == 4 ? 8 : 16)), 0); PROFT(u == 0 ? 7 : (u == 4 ? 15 : 19)); }
          tma_load3(sb + OFF_X + xs.slot * XS, &p.hl2, BAR(B_FX) + 8 * xs.slot, 0, r0, 2 * u);
          if (u == 3) mbar_arrive(BAR(B_XI));
          xs.adv<5>(1);
        }
      }
    } else if (warp == 15) {
      const int g1lo = max(rt - 1, 0), g1hi = min(rt + 1, 25), g2lo = r3 / 80, g2hi = min(25, (r3 + 151) / 80), g3lo = r0 / 152, g3hi = min(13, (r0 + 79) / 152);
#pragma unroll 1
      for (int d = 0; d < 10; d++) {
        int c; unsigned n;
        if (d == 0) { c = C_BAR1 + (lane & 15); n = (lane & 15) < 2 ? 9 : 8; }
        else if (d == 1) { c = C_BAR2 + (lane & 15); n = 24; if (hasC) mbar_wait(BAR(B_CD), 0); }
        else if (d == 2) { c = C_T + ((GSYNC & 1) ? min(lane, 25) : rt); n = 10; }
        else if (d < 5) { c = C_G1 + 26 * (d - 3) + (((GSYNC & 2) && d == 3) ? min(lane, 25) : min(g1lo + lane, g1hi)); n = 5; }
        else if (d < 7) { if (!has3) continue; c = C_G2 + 26 * (d - 5) + (((GSYNC & 4) && d == 5) ? min(lane, 25) : min(g2lo + lane, g2hi)); n = 5; }
        else { c = C_G3 + 14 * (d - 7) + (((GSYNC & 8) && d == 7) ? min(lane, 13) : min(g3lo + lane, g3hi)); n = 9; }
        wait_cnt_w(CNT(c), e1 * n);
        if (lane == 0) mbar_arrive(BAR(B_DEP) + 8 * d);
      }
    } else if (warp == 13) {
      mbar_wait(BAR(B_QT), 0);
#pragma unroll 1
      for (int n = lane; n < 160; n += 32) { const int hf = n >= 80; row_stats(sb + OFF_QT + hf * 10240, sb + OFF_PQ + hf * 640, n - 80 * hf); }
      fence_async_smem();
      __syncwarp();
      if (lane == 0) {
        mbar_arrive(BAR(B_QD));
        bulk_store(&g_st[0][ft][r0], sb + OFF_PQ, 640); bulk_store(&g_st[0][ft + 5][r0], sb + OFF_PQ + 640, 640);
        bulk_commit(); bulk_wait0(); red_cnt(CNT(C_SQ + rt)); PROFT(23);
      }
      __syncwarp();
      if (has3) {
        wait_cnt_w(CNT(C_SX + min(r3 / 80 + lane, min(25, (r3 + 151) / 80))), e1 * 10);
#pragma unroll 1
        for (int r = lane; r < 152; r += 32) { const float2 s = gather_stats(2, r3 + r); const float rs = 0.5f * rsqrtf(s.y + EPS); sts64f(sb + OFF_RP3 + r * 8, rs, -s.x * rs); }
        __syncwarp();
        if (elect_one()) {
          mbar_arrive(BAR(B_RP3)); PROFT(30);
#pragma unroll 1
          for (int w = 0; w < 3; w++) {
            mbar_wait(BAR(B_SG) + 8 * w, 0);
            if (w == GATE) mbar_wait(BAR(B_XI), 0);
            tma_store(&p.hs, sb + OFF_ST, (ft3 + 9 * w) * 64, r3); bulk_commit();
            bulk_wait0();
            red_cnt(CNT(C_G3 + 14 * w + rt3));
            mbar_arrive(BAR(B_SF) + 8 * w);
            PROFT(58 + w);
          }
        }
      }
    } else if (warp == 14) {
      if (elect_one()) {
        Cur ws{0, 0};
        mbar_wait(BAR(B_QT), 0);
        if (hasC && PFMODE == 3) {
          constexpr uint32_t junk = sb + OFF_RED + 3 * RBYTES;
          static_assert(OFF_RED + 3 * RBYTES + 17280 <= OFF_MISC, "junk");
          mbar_expect(BAR(B_PF), 2 * (6400 + 17280));
          bulk_load(junk, p.w1p + (size_t)b * 3200, 6400, BAR(B_PF));
          bulk_load(junk, p.w3p + (size_t)b * 8640, 17280, BAR(B_PF));
          bulk_load(junk, p.w2p + (size_t)b * 3200, 6400, BAR(B_PF));
          bulk_load(junk, p.w4p + (size_t)b * 8640, 17280, BAR(B_PF));
        }
        if (hasC && PFMODE == 0) {
          bulk_prefetch(p.w1p + (size_t)b * 3200, 6400);
          bulk_prefetch(p.w3p + (size_t)b * 8640, 17280);
          bulk_prefetch(p.w2p + (size_t)b * 3200, 6400);
          bulk_prefetch(p.w4p + (size_t)b * 8640, 17280);
        }
#pragma unroll 1
        for (int i = 0; i < 20; i++) {
          if (i < WFREE) __nanosleep(400);
          if (i == WFREE) { mbar_wait(BAR(WLATE ? B_DEP + 2 : B_YT), 0); mbar_wait(BAR(B_QD), 0); }
          const int e = (int)(unit_order(2) >> (4 * (i < 10 ? i : i - 10))) & 15, w = e >= 5;
          w_unit(ws, i < 10 ? &p.w1 : &p.w2, (ft + 5 * w) * 64, (e - 5 * w) * 128);
        }
        if (has3) {
#pragma unroll 1
          for (int i = 0; i < 15; i++) {
            const int e = (int)(unit_order(3) >> (4 * i)) & 15, w = (e >= 5) + (e >= 10);
            w_unit(ws, &p.w3, (ft3 + 9 * w) * 64, (e - 5 * w) * 128);
          }
        }
#pragma unroll 1
        for (int i = 0; i < 27; i++) {
          if (i < NWU) mbar_wait(BAR(B_EW) + 8 * ws.slot, ws.par ^ 1); else mbar_wait(BAR(B_E4) + 8 * ws.slot, (i / NWU - 1) & 1);
          mbar_expect(BAR(B_FW) + 8 * ws.slot, WU);
          tma_load3(sb + OFF_W + ws.slot * WU, &p.w4, BAR(B_FW) + 8 * ws.slot, ft * 64, i * 64, 0);
          ws.adv<NWU>(1);
        }
      }
    }
    return;
  }

  const int g = lane >> 2, t = lane & 3, w4 = warp & 3, tid7 = tid & 127;
  const bool leader = tid7 == 0;
  {
    uint2 ka[4], kb[4]; uint32_t pa[4], pb[4];
    if (hasC) {
      conv_fetch(p.ssm, b * 5 + wg, ka, pa);
      if (wg < 2) conv_fetch(p.ssm, b * 5 + wg + 3, kb, pb);
    }
    __syncthreads();
    if (hasC) {
      conv_build(sb, wg, ka, pa);
      if (wg < 2) conv_build(sb, wg + 3, kb, pb);
      fence_async_smem();
    }
  }
  asm volatile("setmaxnreg.inc.sync.aligned.u32 152;");
  if (hasC) {
    bar_sync(1 + wg, 128);
    PROF0(34 + wg);
#pragma unroll 1
    for (int slot = wg; slot < 5; slot += 3) conv_channel(sb, slot, wg, b * 5 + slot, zero, __bfloat162float(p.ssd[b * 5 + slot]), &p.y80, TST);
    if (w4 == 0 && elect_one()) { bulk_wait0(); red_cnt(CNT(C_BAR2 + (b & 15))); mbar_arrive(BAR(B_CD)); PROFT(37 + wg); }
    __syncwarp();
  }

  if (wg == 2) {
    if (b < 74) {
      const int ld = b < 54 ? FF : D;
      const __nv_bfloat16* src = (b < 54 ? p.w3p + b * 32 : p.w1p + (b - 54) * 32) + (size_t)(tid7 >> 2) * ld + (lane & 3) * 8;
      float s[8];
#pragma unroll
      for (int i = 0; i < 8; i++) s[i] = 0.f;
#pragma unroll 1
      for (int it = 0; it < 4; it++) {
        uint4 u[5];
#pragma unroll
        for (int i = 0; i < 5; i++) u[i] = ldg128(src + (size_t)(it * 5 + i) * 32 * ld);
#pragma unroll
        for (int i = 0; i < 5; i++) {
          s[0] += blo(u[i].x); s[1] += bhi(u[i].x); s[2] += blo(u[i].y); s[3] += bhi(u[i].y);
          s[4] += blo(u[i].z); s[5] += bhi(u[i].z); s[6] += blo(u[i].w); s[7] += bhi(u[i].w);
        }
      }
#pragma unroll
      for (int i = 0; i < 8; i++) {
#pragma unroll
        for (int o = 4; o < 32; o <<= 1) s[i] += __shfl_xor_sync(0xffffffffu, s[i], o);
      }
      const uint32_t R = sb + OFF_CS;
      if (lane < 4) { sts128f(R + w4 * 128 + lane * 32, s[0], s[1], s[2], s[3]); sts128f(R + w4 * 128 + lane * 32 + 16, s[4], s[5], s[6], s[7]); }
      bar_sync(3, 128);
      if (w4 == 0) {
        float a = 0.f;
#pragma unroll
        for (int i = 0; i < 4; i++) a += __uint_as_float(lds32(R + i * 128 + lane * 4));
        sts32f(R + 512 + lane * 4, a);
        fence_async_smem();
        __syncwarp();
        if (elect_one()) { bulk_store(&g_cs[b * 32], R + 512, 128); bulk_commit(); bulk_wait0(); red_cnt(CNT(C_CS)); PROFT(31); }
        __syncwarp();
      }
    }
    {
      const unsigned e1 = lds32(sb + OFF_EP);
      if (w4 < 3) {
        wait_cnt_w(CNT(C_SQ + rt), e1 * 5);
        { const int r = min(tid7, 79); const float2 s = gather_stats(0, r0 + r); sts64f(sb + OFF_RQ + r * 8, s.x, rsqrtf(s.y + EPS)); }
        bar_sync(7, 96);
        mbar_arrive_if(BAR(B_QS), leader);
        PROF0(28);
        wait_cnt_w(CNT(C_SH + rt), e1 * 10);
        {
          const int r = min(tid7, 79);
          const float2 s = gather_stats(1, r0 + r);
          const float r1 = rsqrtf(s.y + EPS), r2 = 0.5f * r1 * rsqrtf(s.y * r1 * r1 + EPS);
          sts64f(sb + OFF_RP + r * 8, r2, -s.x * r2); sts64f(sb + OFF_RP + 640 + r * 8, r1, -s.x * r1);
        }
      } else {
        wait_cnt_w(CNT(C_CS), e1 * 74);
        const float4 c = ldcg128f(&g_cs[FF + (ft + 5 * (lane >> 4)) * 64 + (lane & 15) * 4]);
        sts128f(sb + OFF_C1 + lane * 16, c.x, c.y, c.z, c.w);
      }
      bar_sync(3, 128);
      mbar_arrive_if(BAR(B_RP), leader);
      PROF0(29);
    }
    if (has3) bar_sync(8, 256);
  }

  float res[40];
  uint32_t hp[20];
  const int f0 = (ft + 5 * wg) * 64;
  const uint32_t stg = sb + OFF_ST + wg * 10240;
  if (wg < 2) {
#pragma unroll
  for (int ph = 0; ph < 3; ph++) {
    uint32_t pk[20];
    if (ph == 0) {
      mbar_wait_u(BAR(B_QT), 0);
      const uint32_t qa = tile_addr(sb + OFF_QT + wg * 10240);
#pragma unroll
      for (int j = 0; j < 10; j += 2) ldsm4t(qa + j * 1024, hp[2 * j], hp[2 * j + 1], hp[2 * j + 2], hp[2 * j + 3]);
      bar_sync(1 + wg, 128);
      mbar_arrive_if(BAR(B_QD), leader);
      mbar_wait_u(BAR(B_QS), 0);
#pragma unroll
      for (int j = 0; j < 10; j++) {
        const float4 st = lds128f(sb + OFF_RQ + (8 * j + 2 * t) * 8);
        res[4 * j] = (blo(hp[2 * j]) - st.x) * st.y; res[4 * j + 1] = (bhi(hp[2 * j]) - st.z) * st.w;
        res[4 * j + 2] = (blo(hp[2 * j + 1]) - st.x) * st.y; res[4 * j + 3] = (bhi(hp[2 * j + 1]) - st.z) * st.w;
      }
      const uint32_t ya = sb + OFF_YT + (64 * wg + 16 * w4 + (lane & 15)) * 160 + (lane >> 4) * 16;
      mbar_wait_u(BAR(B_YT), 0);
      PROF0(40);
#pragma unroll
      for (int j = 0; j < 10; j += 2) {
        uint32_t y[4];
        ldsm4(ya + j * 16, y[0], y[1], y[2], y[3]);
#pragma unroll
        for (int m = 0; m < 4; m++)
          hp[2 * j + m] = pack2(fmaf(res[4 * j + 2 * m], blo(y[m]), blo(hp[2 * j + m])), fmaf(res[4 * j + 2 * m + 1], bhi(y[m]), bhi(hp[2 * j + m])));
      }
#pragma unroll
      for (int i = 0; i < 20; i++) pk[i] = hp[i];
    } else {
      if (ph == 1) mma_g12<1>(res, wg, leader, TST, 64 + 10 * wg); else mma_g12<2>(res, wg, leader, TST, 84 + 10 * wg);
      PROF0(ph == 1 ? 42 + wg : 48 + wg);
      if (ph == 1) {
        mbar_wait_u(BAR(B_RP), 0);
        const float c10 = __uint_as_float(lds32(sb + OFF_C1 + (64 * wg + 16 * w4 + g) * 4)), c11 = __uint_as_float(lds32(sb + OFF_C1 + (64 * wg + 16 * w4 + g + 8) * 4));
#pragma unroll
        for (int j = 0; j < 10; j++) {
          const float4 rp = lds128f(sb + OFF_RP + (8 * j + 2 * t) * 8);
          pk[2 * j] = pack2(gelu_half(fmaf(res[4 * j], rp.x, rp.y * c10)), gelu_half(fmaf(res[4 * j + 1], rp.z, rp.w * c10)));
          pk[2 * j + 1] = pack2(gelu_half(fmaf(res[4 * j + 2], rp.x, rp.y * c11)), gelu_half(fmaf(res[4 * j + 3], rp.z, rp.w * c11)));
        }
        PROF0(44 + wg);
      } else {
        if (has3 && wg == 1) bar_arrive(8, 256);
#pragma unroll
        for (int i = 0; i < 20; i++) pk[i] = pack2(res[2 * i], res[2 * i + 1]);
      }
    }
    stage_tile<10>(stg, pk);
    fence_async_smem();
    bar_sync(1 + wg, 128);
    if (w4 == 3 && elect_one()) {
      tma_store(&p.h + ph, stg, f0, r0); bulk_commit(); bulk_wait0();
      red_cnt(CNT((ph == 0 ? C_T : (ph == 1 ? C_G1 : C_G2) + 26 * wg) + rt));
      PROFT(154 + 2 * ph + wg);
    }
    __syncwarp();
    if (ph == 0) {
#pragma unroll
      for (int i = 0; i < 40; i++) res[i] = 0.f;
    } else if (ph == 1) {
#pragma unroll
      for (int j = 0; j < 10; j++) {
        const float4 rp = lds128f(sb + OFF_RP + 640 + (8 * j + 2 * t) * 8);
        res[4 * j] = fmaf(blo(hp[2 * j]), rp.x, rp.y); res[4 * j + 1] = fmaf(bhi(hp[2 * j]), rp.z, rp.w);
        res[4 * j + 2] = fmaf(blo(hp[2 * j + 1]), rp.x, rp.y); res[4 * j + 3] = fmaf(bhi(hp[2 * j + 1]), rp.z, rp.w);
      }
    } else {
#pragma unroll
      for (int i = 0; i < 20; i++) { res[2 * i] = blo(pk[i]) + blo(hp[i]); res[2 * i + 1] = bhi(pk[i]) + bhi(hp[i]); }
    }
    if (!(ph & 1) && w4 < 3) {
      row_stats(stg, sb + OFF_PS + wg * 640, min(tid7, 79));
      fence_async_smem();
      bar_sync(5 + wg, 96);
      if (w4 == 0 && elect_one()) { bulk_store(&g_st[1 + (ph >> 1)][f0 >> 6][r0], sb + OFF_PS + wg * 640, 640); bulk_commit(); bulk_wait0(); red_cnt(CNT((ph == 0 ? C_SH : C_SX) + rt)); }
      __syncwarp();
    }
  }
  }
  if (has3) {
        const int f3 = (ft3 + 9 * wg) * 64;
        const float cs0 = ldcg32f(&g_cs[f3 + 16 * w4 + g]), cs1 = ldcg32f(&g_cs[f3 + 16 * w4 + g + 8]);
        float acc[76];
#pragma unroll
        for (int i = 0; i < 76; i++) acc[i] = 0.f;
        mma_g3(acc, wg, leader, TST, 104 + 10 * wg);
        PROF0(52 + wg);
        mbar_wait_u(BAR(B_RP3), 0);
        uint32_t pq[38];
#pragma unroll
        for (int j = 0; j < 19; j++) {
          const float4 rp = lds128f(sb + OFF_RP3 + (8 * j + 2 * t) * 8);
          pq[2 * j] = pack2(gelu_half(fmaf(acc[4 * j], rp.x, rp.y * cs0)), gelu_half(fmaf(acc[4 * j + 1], rp.z, rp.w * cs0)));
          pq[2 * j + 1] = pack2(gelu_half(fmaf(acc[4 * j + 2], rp.x, rp.y * cs1)), gelu_half(fmaf(acc[4 * j + 3], rp.z, rp.w * cs1)));
        }
        PROF0(55 + wg);
        if (wg > 0) mbar_wait_u(BAR(B_SF + wg - 1), 0);
        stage_tile<19>(sb + OFF_ST, pq);
        fence_async_smem();
        bar_sync(1 + wg, 128);
        mbar_arrive_if(BAR(B_SG + wg), leader);
      }
  if (wg < 2) {
    mma_g4(res, wg, has3 ? 35 : 20, leader, TST, 134 + 10 * wg);
    PROF0(61);
    uint32_t pk[20];
#pragma unroll
    for (int i = 0; i < 20; i++) pk[i] = pack2(res[2 * i], res[2 * i + 1]);
    if (has3) mbar_wait_u(BAR(B_SF + 2), 0);
    stage_tile<10>(stg, pk);
    fence_async_smem();
    bar_sync(1 + wg, 128);
    if (w4 == 0 && elect_one()) {
      tma_store(&p.out, stg, f0, r0); bulk_commit(); bulk_wait0(); PROFT(62 + wg);
    }
  }
}

typedef CUresult (*EncFn)(CUtensorMap*, CUtensorMapDataType, cuuint32_t, void*, const cuuint64_t*, const cuuint64_t*, const cuuint32_t*,
                          const cuuint32_t*, CUtensorMapInterleave, CUtensorMapSwizzle, CUtensorMapL2promotion, CUtensorMapFloatOOBfill);
void make_map(EncFn enc, CUtensorMap* tm, const void* ptr, int cols, int rows, int bc, int br, CUtensorMapSwizzle sw) {
  cuuint64_t gd[2] = {(cuuint64_t)cols, (cuuint64_t)rows}, gs[1] = {(cuuint64_t)cols * 2};
  cuuint32_t bd[2] = {(cuuint32_t)bc, (cuuint32_t)br}, es[2] = {1, 1};
  enc(tm, CU_TENSOR_MAP_DATA_TYPE_BFLOAT16, 2, const_cast<void*>(ptr), gd, gs, bd, es, CU_TENSOR_MAP_INTERLEAVE_NONE, sw,
      CU_TENSOR_MAP_L2_PROMOTION_L2_128B, CU_TENSOR_MAP_FLOAT_OOB_FILL_NONE);
}
void make_map2(EncFn enc, CUtensorMap* tm, const void* ptr, int cols) {
  cuuint64_t gd[3] = {64, (cuuint64_t)S, (cuuint64_t)cols / 64}, gs[2] = {(cuuint64_t)cols * 2, 128};
  cuuint32_t bd[3] = {64, 80, 2}, es[3] = {1, 1, 1};
  enc(tm, CU_TENSOR_MAP_DATA_TYPE_BFLOAT16, 3, const_cast<void*>(ptr), gd, gs, bd, es, CU_TENSOR_MAP_INTERLEAVE_NONE, CU_TENSOR_MAP_SWIZZLE_128B,
      CU_TENSOR_MAP_L2_PROMOTION_L2_128B, CU_TENSOR_MAP_FLOAT_OOB_FILL_NONE);
}
template <class T> void* sym_addr(T& s) { void* a = nullptr; cudaGetSymbolAddress(&a, s); return a; }

}

extern "C" void kernel_launch(void* const* d_in, const int* in_sizes, int n_in, void* d_out, int out_size) {
  (void)in_sizes; (void)n_in; (void)out_size;
  void* fn = nullptr; cudaDriverEntryPointQueryResult qr;
  cudaGetDriverEntryPoint("cuTensorMapEncodeTiled", &fn, cudaEnableDefault, &qr);
  EncFn enc = (EncFn)fn;
  Params p;
  typedef const __nv_bfloat16* BP;
  p.q = (BP)d_in[0]; p.k = (BP)d_in[1]; p.v = (BP)d_in[2]; p.shk = (BP)d_in[3]; p.ssm = (BP)d_in[4]; p.ssd = (BP)d_in[5];
  p.w1p = (BP)d_in[7]; p.w2p = (BP)d_in[8]; p.w3p = (BP)d_in[9]; p.w4p = (BP)d_in[10];
  const CUtensorMapSwizzle S128 = CU_TENSOR_MAP_SWIZZLE_128B, S64 = CU_TENSOR_MAP_SWIZZLE_64B, S0 = CU_TENSOR_MAP_SWIZZLE_NONE;
  make_map(enc, &p.w1, p.w1p, D, D, 64, 128, S128);
  make_map(enc, &p.w2, p.w2p, D, D, 64, 128, S128);
  make_map(enc, &p.w3, p.w3p, FF, D, 64, 128, S128);
  {
    cuuint64_t gd[3] = {320, (cuuint64_t)FF, 2}, gs[2] = {(cuuint64_t)D * 2, 640};
    cuuint32_t bd[3] = {64, 64, 2}, es[3] = {1, 1, 1};
    enc(&p.w4, CU_TENSOR_MAP_DATA_TYPE_BFLOAT16, 3, const_cast<__nv_bfloat16*>(p.w4p), gd, gs, bd, es, CU_TENSOR_MAP_INTERLEAVE_NONE, S128,
        CU_TENSOR_MAP_L2_PROMOTION_L2_128B, CU_TENSOR_MAP_FLOAT_OOB_FILL_NONE);
  }
  {
    cuuint64_t gd[4] = {1024, 80, 2, 8}, gs[3] = {32768, 2048, 4096};
    cuuint32_t bd[4] = {80, 8, 2, 8}, es[4] = {1, 1, 1, 1};
    enc(&p.kv, CU_TENSOR_MAP_DATA_TYPE_BFLOAT16, 4, sym_addr(g_kvT), gd, gs, bd, es, CU_TENSOR_MAP_INTERLEAVE_NONE, S0,
        CU_TENSOR_MAP_L2_PROMOTION_NONE, CU_TENSOR_MAP_FLOAT_OOB_FILL_NONE);
  }
  make_map(enc, &p.q80, p.q, D, S, 64, 80, S128);
  {
    cuuint64_t gd[3] = {80, (cuuint64_t)D, 26}, gs[2] = {160, (cuuint64_t)D * 160};
    cuuint32_t bd[3] = {80, 1, 26}, es[3] = {1, 1, 1};
    enc(&p.y80, CU_TENSOR_MAP_DATA_TYPE_BFLOAT16, 3, sym_addr(g_yB), gd, gs, bd, es, CU_TENSOR_MAP_INTERLEAVE_NONE, S0,
        CU_TENSOR_MAP_L2_PROMOTION_NONE, CU_TENSOR_MAP_FLOAT_OOB_FILL_NONE);
  }
  make_map(enc, &p.h, sym_addr(g_h), D, S, 64, 80, S128);
  make_map(enc, &p.h1, sym_addr(g_h1), D, S, 64, 80, S128);
  make_map(enc, &p.h1n, sym_addr(g_h1), D, S, 32, 80, S64);
  make_map(enc, &p.x1s, sym_addr(g_x1), D, S, 64, 80, S128);
  make_map(enc, &p.x1l, sym_addr(g_x1), D, S, 64, 152, S128);
  make_map(enc, &p.hs, sym_addr(g_hid), FF, S, 64, 152, S128);
  make_map2(enc, &p.hl2, sym_addr(g_hid), FF);
  make_map2(enc, &p.h2, sym_addr(g_h), D);
  make_map(enc, &p.out, d_out, D, S, 64, 80, S128);
  cudaFuncSetAttribute(fused_kernel, cudaFuncAttributeMaxDynamicSharedMemorySize, SMEM_BYTES);
  fused_kernel<<<NCTA, NTHR, SMEM_BYTES, cudaStreamPerThread>>>(p, 0u);
}
```

```cpp
#include <cuda_runtime.h>
#include <cuda.h>
#include <cuda_bf16.h>
#include <stdint.h>

namespace {

constexpr int S = 2048, D = 640, FF = 1728;
constexpr int NCTA = 130, NTHR = 512;
constexpr float EPS = 1e-5f;
#define RED16 1
#define GSYNC 24
#define MAP3 1
#define WEARLY 4
#define WEARLY4 4
#define DRY 1
#define PFMODE 3
#define EXPT 0
#define GATE 3
#define WLATE 2
#define PD3 3
#define PD1 5
#define TANHV 1
#define SPLIT0 1
#define CHAIN 1
#define XEARLY 3
#define POLLP 0
#define CTOK 1
#define DFOLD 1
#define HRED 0
#define P2 0
#define KVSPLIT 0
#define XWIN 3
#define JOINT1 0
#define JOINT2 2
#define JOINT3 3
#define PAUSE2 1
#define PK3 14
#define LSG 0x3fc
#define MAP2 0
#define TALIGN 0
#define TOK3H 1

constexpr int NWU = 6, WU = 16384;
constexpr int OFF_W = 0;
constexpr int OFF_X = NWU * WU;
constexpr int XS = 20480;
constexpr int OFF_ST = OFF_X + 5 * XS;
constexpr int OFF_MISC = OFF_ST + 20480;
constexpr int OFF_BAR = OFF_MISC;
constexpr int OFF_RP = OFF_MISC + 640;
constexpr int OFF_RP3 = OFF_RP + 1280;
constexpr int OFF_RQ = OFF_RP3 + 1280;
constexpr int OFF_PS = OFF_RQ + 640;
constexpr int OFF_PQ = OFF_PS + 1280;
constexpr int OFF_CS = OFF_PQ + 1280;
constexpr int OFF_C1 = OFF_CS + 640;
constexpr int OFF_EP = OFF_C1 + 512;
constexpr int SMEM_BYTES = 232448;
static_assert(OFF_EP + 16 <= SMEM_BYTES, "smem");
constexpr int OFF_KV = 0;
constexpr int OFF_QT = 71680;
constexpr int OFF_YT = OFF_X + 4 * XS;
constexpr int CB = P2 ? 51200 : 92160;
constexpr int PBYTES = P2 ? 16512 : 8448, XBYTES = 4352, XLBO = 2176, RBYTES = RED16 ? 10752 : 21504;
constexpr int OFF_P = CB, OFF_XC = CB + 5 * PBYTES, OFF_RED = OFF_XC + 5 * XBYTES;
static_assert(OFF_RED + 3 * RBYTES <= OFF_MISC, "conv overlay");
constexpr int WFREE = 4;
constexpr int B_FW = 0, B_EW = 6, B_FX = 12  , B_EX = 18  , B_XC = 24, B_CD = 29, B_QT = 30, B_QS = 31, B_YT = 32, B_QD = 33, B_RP = 34,
              B_RP3 = 35, B_TA = 36  , B_K1 = 38, B_K2 = 39, B_K3 = 70  , B_SF = 41  , B_DEP = 44  , B_PF = 55, B_SG = 56  ,
              B_XI = 60, B_E4 = 61  , B_SR = 67, B_GC = 68  , B_LS = 72  , NBAR = 80;
#define BAR(i) (sb + OFF_BAR + 8 * (i))
constexpr uint32_t SB = 1024;

struct alignas(64) Params {
  CUtensorMap w1, w2, w3, w4, kv, q80, y80, h, h1, x1s, out, h2, h1n, x1l, hs, hs72, hl2;
  const __nv_bfloat16 *q, *k, *v, *shk, *ssm, *ssd, *w1p, *w2p, *w3p, *w4p;
};

constexpr int SP = S + 128;
__device__ __align__(1024) __nv_bfloat16 g_kvT[D * S];
__device__ __align__(1024) __nv_bfloat16 g_yB[26 * D * 80];
__device__ __align__(1024) __nv_bfloat16 g_h[S * D];
__device__ __align__(1024) __nv_bfloat16 g_h1[S * D];
__device__ __align__(1024) __nv_bfloat16 g_x1[S * D];
__device__ __align__(1024) __nv_bfloat16 g_hid[S * FF];
__device__ __align__(128) float2 g_st[3][10][SP];
__device__ __align__(128) float g_cs[FF + D];
__device__ __align__(128) unsigned g_cnt[256 * 32];
__device__ unsigned g_epoch;
constexpr int C_KV = 0  , C_Y = 10  , C_T = 20  , C_G1 = 46  , C_G2 = 98  , C_G3 = 150  , C_SQ = 153, C_SH = 179,
              C_SX = 205, C_CS = 231;
#define CNT(f, i) (&g_cnt[(f) * 32 + (i)])
#define PROFT(i) do { } while (0)
#define PROF0(i) do { } while (0)
#define TST 0

__device__ __forceinline__ uint32_t s2u(const void* p) { return (uint32_t)__cvta_generic_to_shared(p); }
__device__ __forceinline__ void mbar_init(uint32_t b, int c) { asm volatile("mbarrier.init.shared::cta.b64 [%0], %1;" ::"r"(b), "r"(c) : "memory"); }
__device__ __forceinline__ void mbar_expect(uint32_t b, int bytes) { asm volatile("mbarrier.arrive.expect_tx.shared::cta.b64 _, [%0], %1;" ::"r"(b), "r"(bytes) : "memory"); }
__device__ __forceinline__ void mbar_arrive(uint32_t b) { asm volatile("mbarrier.arrive.shared::cta.b64 _, [%0];" ::"r"(b) : "memory"); }
__device__ __forceinline__ void mbar_arrive_n(uint32_t b, int n) { asm volatile("mbarrier.arrive.shared::cta.b64 _, [%0], %1;" ::"r"(b), "r"(n) : "memory"); }
__device__ __forceinline__ bool mbar_try(uint32_t b, uint32_t parity) {
  uint32_t ok;
  asm volatile("{\n.reg .pred p;\nmbarrier.try_wait.parity.shared::cta.b64 p, [%1], %2;\nselp.u32 %0, 1, 0, p;\n}" : "=r"(ok) : "r"(b), "r"(parity) : "memory");
  return ok;
}
__device__ __forceinline__ void mbar_wait(uint32_t b, uint32_t parity) {
  int it = 0;
#pragma unroll 1
  while (!mbar_try(b, parity)) { if (++it > (1 << 20)) break; }
}
__device__ __forceinline__ void mbar_wait_u(uint32_t b, uint32_t parity) {
  int it = 0;
#pragma unroll 1
  while (!__all_sync(0xffffffffu, mbar_try(b, parity))) { if (++it > (1 << 20)) break; }
}
#define mbar_wait1 mbar_wait_u
__device__ __forceinline__ void mbar_wait2(uint32_t a, uint32_t pa, uint32_t b, uint32_t pb) {
  int it = 0;
#pragma unroll 1
  while (true) {
    uint32_t ok;
    asm volatile("{\n.reg .pred p, q;\nmbarrier.try_wait.parity.shared::cta.b64 p, [%1], %2;\nmbarrier.try_wait.parity.shared::cta.b64 q, [%3], %4;\n"
                 "and.pred p, p, q;\nselp.u32 %0, 1, 0, p;\n}" : "=r"(ok) : "r"(a), "r"(pa), "r"(b), "r"(pb) : "memory");
    if (__all_sync(0xffffffffu, ok) || ++it > (1 << 20)) break;
  }
}
__device__ __forceinline__ void mbar_arrive_if(uint32_t b, bool c) {
  asm volatile("{\n.reg .pred p;\nsetp.ne.u32 p, %1, 0;\n@p mbarrier.arrive.shared::cta.b64 _, [%0];\n}" ::"r"(b), "r"((uint32_t)c) : "memory");
}
__device__ __forceinline__ void mbar_arrive_n_if(uint32_t b, uint32_t n, bool c) {
  asm volatile("{\n.reg .pred p;\nsetp.ne.u32 p, %2, 0;\n@p mbarrier.arrive.shared::cta.b64 _, [%0], %1;\n}" ::"r"(b), "r"(n), "r"((uint32_t)c) : "memory");
}
template <bool TWO>
__device__ __forceinline__ uint32_t try2_wait1_release(uint32_t a, uint32_t pa, uint32_t b, uint32_t pb, uint32_t rx, uint32_t n, bool rel) {
  uint32_t ok;
  if (TWO)
    asm volatile("{\n.reg .pred p, q, r;\nsetp.ne.u32 r, %7, 0;\nmbarrier.test_wait.parity.shared::cta.b64 p, [%1], %2;\nmbarrier.test_wait.parity.shared::cta.b64 q, [%3], %4;\n"
                 "wgmma.wait_group.sync.aligned 1;\n@r mbarrier.arrive.shared::cta.b64 _, [%5], %6;\n"
                 "@r mbarrier.arrive.shared::cta.b64 _, [%5 + 8], %6;\nand.pred p, p, q;\nselp.u32 %0, 1, 0, p;\n}"
                 : "=r"(ok) : "r"(a), "r"(pa), "r"(b), "r"(pb), "r"(rx), "r"(n), "r"((uint32_t)rel) : "memory");
  else
    asm volatile("{\n.reg .pred p, q, r;\nsetp.ne.u32 r, %7, 0;\nmbarrier.test_wait.parity.shared::cta.b64 p, [%1], %2;\nmbarrier.test_wait.parity.shared::cta.b64 q, [%3], %4;\n"
                 "wgmma.wait_group.sync.aligned 1;\n@r mbarrier.arrive.shared::cta.b64 _, [%5], %6;\n"
                 "and.pred p, p, q;\nselp.u32 %0, 1, 0, p;\n}"
                 : "=r"(ok) : "r"(a), "r"(pa), "r"(b), "r"(pb), "r"(rx), "r"(n), "r"((uint32_t)rel) : "memory");
  return ok;
}
__device__ __forceinline__ unsigned ld_cnt(const unsigned* p) { unsigned v; asm volatile("ld.relaxed.gpu.global.u32 %0, [%1];" : "=r"(v) : "l"(p) : "memory"); return v; }
__device__ __forceinline__ void wait_cnt(const unsigned* p, unsigned target) {
  int it = 0;
  while ((int)(ld_cnt(p) - target) < 0) { if (++it > (1 << 20)) break; }
}
__device__ __forceinline__ void wait_cnt3(const unsigned* p0, const unsigned* p1, const unsigned* p2, unsigned target) {
  int it = 0;
  while (true) {
    const unsigned a = ld_cnt(p0), b = ld_cnt(p1), c = ld_cnt(p2);
    if (((int)(a - target) | (int)(b - target) | (int)(c - target)) >= 0) break;
    if (++it > (1 << 20)) break;
  }
}
__device__ __forceinline__ void wait_cnt_w(const unsigned* p, unsigned target) {
  int it = 0;
  while (!__all_sync(0xffffffffu, (int)(ld_cnt(p) - target) >= 0)) {
    if (++it > (1 << 20)) break;
  }
}
__device__ __forceinline__ void wait_cnt_p(const unsigned* p, unsigned target) {
  unsigned a = ld_cnt(p), b;
  { const long long t0 = clock64(); while (clock64() - t0 < 250) { } }
#pragma unroll 1
  for (int it = 0; it < (1 << 20); it++) {
    b = ld_cnt(p);
    if (__all_sync(0xffffffffu, (int)(a - target) >= 0)) break;
    a = ld_cnt(p);
    if (__all_sync(0xffffffffu, (int)(b - target) >= 0)) break;
  }
}
__device__ __forceinline__ unsigned gtime32() { unsigned t; asm volatile("mov.u32 %0, %%globaltimer_lo;" : "=r"(t)); return t; }
__device__ __forceinline__ void red_cnt(unsigned* p) { asm volatile("red.relaxed.gpu.global.add.u32 [%0], 1;" ::"l"(p) : "memory"); }
__device__ __forceinline__ void bar_arrive(int id, int n) { asm volatile("bar.arrive %0, %1;" ::"r"(id), "r"(n) : "memory"); }
__device__ __forceinline__ void tma_store3(const CUtensorMap* tm, uint32_t src, int c0, int c1, int c2) {
  asm volatile("cp.async.bulk.tensor.3d.global.shared::cta.bulk_group [%0, {%2, %3, %4}], [%1];" ::"l"(tm), "r"(src), "r"(c0), "r"(c1), "r"(c2) : "memory");
}
__device__ __forceinline__ void tma_store4(const CUtensorMap* tm, uint32_t src, int c0, int c1, int c2, int c3) {
  asm volatile("cp.async.bulk.tensor.4d.global.shared::cta.bulk_group [%0, {%2, %3, %4, %5}], [%1];" ::"l"(tm), "r"(src), "r"(c0), "r"(c1), "r"(c2), "r"(c3) : "memory");
}
__device__ __forceinline__ void ldsm4(uint32_t a, uint32_t& r0, uint32_t& r1, uint32_t& r2, uint32_t& r3) {
  asm volatile("ldmatrix.sync.aligned.m8n8.x4.shared.b16 {%0,%1,%2,%3}, [%4];" : "=r"(r0), "=r"(r1), "=r"(r2), "=r"(r3) : "r"(a) : "memory");
}
__device__ __forceinline__ void sts64u(uint32_t a, uint32_t x, uint32_t y) { asm volatile("st.shared.v2.b32 [%0], {%1,%2};" ::"r"(a), "r"(x), "r"(y) : "memory"); }
__device__ __forceinline__ void sts32f(uint32_t a, float x) { asm volatile("st.shared.f32 [%0], %1;" ::"r"(a), "f"(x) : "memory"); }
__device__ __forceinline__ void fence_async_all() { asm volatile("fence.proxy.async;" ::: "memory"); }
__device__ __forceinline__ void fence_async_smem() { asm volatile("fence.proxy.async.shared::cta;" ::: "memory"); }
__device__ __forceinline__ void bar_sync(int id, int n) { asm volatile("bar.sync %0, %1;" ::"r"(id), "r"(n) : "memory"); }
__device__ __forceinline__ bool elect_one() {
  uint32_t e; asm volatile("{\n.reg .pred p;\nelect.sync _|p, 0xffffffff;\nselp.u32 %0, 1, 0, p;\n}" : "=r"(e)); return e;
}
__device__ __forceinline__ void tma_load(uint32_t dst, const CUtensorMap* tm, uint32_t bar, int c0, int c1) {
  asm volatile("cp.async.bulk.tensor.2d.shared::cluster.global.mbarrier::complete_tx::bytes [%0], [%1, {%3, %4}], [%2];"
               ::"r"(dst), "l"(tm), "r"(bar), "r"(c0), "r"(c1) : "memory");
}
__device__ __forceinline__ void tma_load3(uint32_t dst, const CUtensorMap* tm, uint32_t bar, int c0, int c1, int c2) {
  asm volatile("cp.async.bulk.tensor.3d.shared::cluster.global.mbarrier::complete_tx::bytes [%0], [%1, {%3, %4, %5}], [%2];"
               ::"r"(dst), "l"(tm), "r"(bar), "r"(c0), "r"(c1), "r"(c2) : "memory");
}
__device__ __forceinline__ void tma_load4(uint32_t dst, const CUtensorMap* tm, uint32_t bar, int c3) {
  asm volatile("cp.async.bulk.tensor.4d.shared::cluster.global.mbarrier::complete_tx::bytes [%0], [%1, {%3, %3, %3, %4}], [%2];"
               ::"r"(dst), "l"(tm), "r"(bar), "r"(0), "r"(c3) : "memory");
}
__device__ __forceinline__ void tma_store(const CUtensorMap* tm, uint32_t src, int c0, int c1) {
  asm volatile("cp.async.bulk.tensor.2d.global.shared::cta.bulk_group [%0, {%2, %3}], [%1];" ::"l"(tm), "r"(src), "r"(c0), "r"(c1) : "memory");
}
__device__ __forceinline__ void bulk_load(uint32_t dst, const void* src, int bytes, uint32_t bar) {
  asm volatile("cp.async.bulk.shared::cluster.global.mbarrier::complete_tx::bytes [%0], [%1], %2, [%3];" ::"r"(dst), "l"(src), "r"(bytes), "r"(bar) : "memory");
}
__device__ __forceinline__ void bulk_store(void* dst, uint32_t src, int bytes) {
  asm volatile("cp.async.bulk.global.shared::cta.bulk_group [%0], [%1], %2;" ::"l"(dst), "r"(src), "r"(bytes) : "memory");
}
__device__ __forceinline__ void bulk_reduce(void* dst, uint32_t src, int bytes) {
  asm volatile("cp.reduce.async.bulk.global.shared::cta.bulk_group.add.f32 [%0], [%1], %2;" ::"l"(dst), "r"(src), "r"(bytes) : "memory");
}
__device__ __forceinline__ uint32_t ldg16(const void* p) { uint32_t v; asm volatile("ld.global.nc.u16 %0, [%1];" : "=r"(v) : "l"(p)); return v; }
__device__ __forceinline__ void bulk_prefetch(const void* src, int bytes) { asm volatile("cp.async.bulk.prefetch.L2.global [%0], %1;" ::"l"(src), "r"(bytes) : "memory"); }
__device__ __forceinline__ void prefetch_l2(const void* p) { asm volatile("prefetch.global.L2 [%0];" ::"l"(p)); }
__device__ __forceinline__ void bulk_commit() { asm volatile("cp.async.bulk.commit_group;" ::: "memory"); }
__device__ __forceinline__ void bulk_wait0() { asm volatile("cp.async.bulk.wait_group 0;" ::: "memory"); }
__device__ __forceinline__ void bulk_wait0_read() { asm volatile("cp.async.bulk.wait_group.read 0;" ::: "memory"); }
__device__ __forceinline__ void wg_fence() { asm volatile("wgmma.fence.sync.aligned;" ::: "memory"); }
__device__ __forceinline__ void wg_commit() { asm volatile("wgmma.commit_group.sync.aligned;" ::: "memory"); }
template <int N> __device__ __forceinline__ void wg_wait() { asm volatile("wgmma.wait_group.sync.aligned %0;" ::"n"(N) : "memory"); }
__device__ __forceinline__ uint64_t mkdesc(uint32_t addr, uint32_t lbo, uint32_t sbo, uint32_t swz) {
  return (uint64_t)((addr & 0x3FFFF) >> 4) | ((uint64_t)(lbo >> 4) << 16) | ((uint64_t)(sbo >> 4) << 32) | ((uint64_t)swz << 62);
}
__device__ __forceinline__ uint32_t lds32(uint32_t a) { uint32_t v; asm volatile("ld.shared.b32 %0, [%1];" : "=r"(v) : "r"(a) : "memory"); return v; }
__device__ __forceinline__ float4 lds128f(uint32_t a) { float4 v; asm volatile("ld.shared.v4.f32 {%0,%1,%2,%3}, [%4];" : "=f"(v.x), "=f"(v.y), "=f"(v.z), "=f"(v.w) : "r"(a) : "memory"); return v; }
__device__ __forceinline__ float2 lds64f(uint32_t a) { float2 v; asm volatile("ld.shared.v2.f32 {%0,%1}, [%2];" : "=f"(v.x), "=f"(v.y) : "r"(a) : "memory"); return v; }
__device__ __forceinline__ void sts128f(uint32_t a, float x, float y, float z, float w) { asm volatile("st.shared.v4.f32 [%0], {%1,%2,%3,%4};" ::"r"(a), "f"(x), "f"(y), "f"(z), "f"(w) : "memory"); }
__device__ __forceinline__ void sts128u(uint32_t a, uint32_t x, uint32_t y, uint32_t z, uint32_t w) { asm volatile("st.shared.v4.b32 [%0], {%1,%2,%3,%4};" ::"r"(a), "r"(x), "r"(y), "r"(z), "r"(w) : "memory"); }
__device__ __forceinline__ void sts64f(uint32_t a, float x, float y) { asm volatile("st.shared.v2.f32 [%0], {%1,%2};" ::"r"(a), "f"(x), "f"(y) : "memory"); }
__device__ __forceinline__ void ldsm4t(uint32_t a, uint32_t& r0, uint32_t& r1, uint32_t& r2, uint32_t& r3) {
  asm volatile("ldmatrix.sync.aligned.m8n8.x4.trans.shared.b16 {%0,%1,%2,%3}, [%4];" : "=r"(r0), "=r"(r1), "=r"(r2), "=r"(r3) : "r"(a) : "memory");
}
__device__ __forceinline__ void stsm4t(uint32_t a, uint32_t r0, uint32_t r1, uint32_t r2, uint32_t r3) {
  asm volatile("stmatrix.sync.aligned.m8n8.x4.trans.shared.b16 [%0], {%1,%2,%3,%4};" ::"r"(a), "r"(r0), "r"(r1), "r"(r2), "r"(r3) : "memory");
}
__device__ __forceinline__ void stsm2t(uint32_t a, uint32_t r0, uint32_t r1) {
  asm volatile("stmatrix.sync.aligned.m8n8.x2.trans.shared.b16 [%0], {%1,%2};" ::"r"(a), "r"(r0), "r"(r1) : "memory");
}
__device__ __forceinline__ uint32_t pack2(float lo, float hi) { uint32_t r; asm("cvt.rn.bf16x2.f32 %0, %1, %2;" : "=r"(r) : "f"(hi), "f"(lo)); return r; }
__device__ __forceinline__ uint32_t hadd2(uint32_t a, uint32_t b) { uint32_t r; asm("add.rn.bf16x2 %0, %1, %2;" : "=r"(r) : "r"(a), "r"(b)); return r; }
__device__ __forceinline__ float blo(uint32_t u) { return __uint_as_float(u << 16); }
__device__ __forceinline__ float bhi(uint32_t u) { return __uint_as_float(u & 0xffff0000u); }
__device__ __forceinline__ uint4 ldg128(const void* p) { uint4 v; asm volatile("ld.global.nc.L1::no_allocate.v4.u32 {%0,%1,%2,%3}, [%4];" : "=r"(v.x), "=r"(v.y), "=r"(v.z), "=r"(v.w) : "l"(p)); return v; }
__device__ __forceinline__ uint4 ldg128c(const void* p) { uint4 v; asm volatile("ld.global.nc.v4.u32 {%0,%1,%2,%3}, [%4];" : "=r"(v.x), "=r"(v.y), "=r"(v.z), "=r"(v.w) : "l"(p)); return v; }
__device__ __forceinline__ uint4 ldcg128(const void* p) { uint4 v; asm volatile("ld.global.cg.v4.u32 {%0,%1,%2,%3}, [%4];" : "=r"(v.x), "=r"(v.y), "=r"(v.z), "=r"(v.w) : "l"(p) : "memory"); return v; }
__device__ __forceinline__ float4 ldcg128f(const void* p) { float4 v; asm volatile("ld.global.cg.v4.f32 {%0,%1,%2,%3}, [%4];" : "=f"(v.x), "=f"(v.y), "=f"(v.z), "=f"(v.w) : "l"(p) : "memory"); return v; }
__device__ __forceinline__ float2 ldcg64f(const void* p) { float2 v; asm volatile("ld.global.cg.v2.f32 {%0,%1}, [%2];" : "=f"(v.x), "=f"(v.y) : "l"(p) : "memory"); return v; }
__device__ __forceinline__ float ldcg32f(const void* p) { float v; asm volatile("ld.global.cg.f32 %0, [%1];" : "=f"(v) : "l"(p) : "memory"); return v; }
__device__ __forceinline__ uint4 lds128u(uint32_t a) { uint4 v; asm volatile("ld.shared.v4.b32 {%0,%1,%2,%3}, [%4];" : "=r"(v.x), "=r"(v.y), "=r"(v.z), "=r"(v.w) : "r"(a) : "memory"); return v; }
__device__ __forceinline__ uint2 lds64u(uint32_t a) { uint2 v; asm volatile("ld.shared.v2.b32 {%0,%1}, [%2];" : "=r"(v.x), "=r"(v.y) : "r"(a) : "memory"); return v; }
template <int OFF> __device__ __forceinline__ float4 lds128f_at(uint32_t a) {
  float4 v; asm volatile("ld.shared.v4.f32 {%0,%1,%2,%3}, [%4 + %5];" : "=f"(v.x), "=f"(v.y), "=f"(v.z), "=f"(v.w) : "r"(a), "n"(OFF) : "memory"); return v;
}
__device__ __forceinline__ float gelu_half(float h) {
  float u = h * fmaf(h * h, 8.f * 0.044715f * 0.7978845608028654f, 2.f * 0.7978845608028654f), t;
  asm volatile("tanh.approx.f32 %0, %1;" : "=f"(t) : "f"(u));
  return fmaf(h, t, h);
}
template <int J, int NJ, int PD> struct GeluRows {
  static __device__ __forceinline__ void run(const float* acc, uint32_t* pk, float4* rp, uint32_t a, float c0, float c1) {
    if (J + PD < NJ) rp[(J + PD) % (PD + 1)] = lds128f_at<(J + PD) * 64>(a);
    const float4 r = rp[J % (PD + 1)];
    pk[2 * J] = pack2(gelu_half(fmaf(acc[4 * J], r.x, r.y * c0)), gelu_half(fmaf(acc[4 * J + 1], r.z, r.w * c0)));
    pk[2 * J + 1] = pack2(gelu_half(fmaf(acc[4 * J + 2], r.x, r.y * c1)), gelu_half(fmaf(acc[4 * J + 3], r.z, r.w * c1)));
  }
};
template <int J0, int J1, int NJ, int PD> __device__ __forceinline__ void gelu_range(const float* acc, uint32_t* pk, float4* rp, uint32_t a, float c0, float c1) {
  if constexpr (J0 < J1) { GeluRows<J0, NJ, PD>::run(acc, pk, rp, a, c0, c1); gelu_range<J0 + 1, J1, NJ, PD>(acc, pk, rp, a, c0, c1); }
}
template <int J, int PD> __device__ __forceinline__ void gelu_prime(float4* rp, uint32_t a) {
  if constexpr (J < PD) { rp[J] = lds128f_at<J * 64>(a); gelu_prime<J + 1, PD>(rp, a); }
}
__device__ __forceinline__ void wgmma_rs_n64(float* d, uint32_t a0, uint32_t a1, uint32_t a2, uint32_t a3, uint64_t db) {
  asm volatile("wgmma.mma_async.sync.aligned.m64n64k16.f32.bf16.bf16 {%0, %1, %2, %3, %4, %5, %6, %7, %8, %9, %10, %11, %12, %13, %14, %15, %16, %17, %18, %19, %20, %21, %22, %23, %24, %25, %26, %27, %28, %29, %30, %31}, {%32, %33, %34, %35}, %36, 1, 1, 1, 0;"
    : "+f"(d[0]), "+f"(d[1]), "+f"(d[2]), "+f"(d[3]), "+f"(d[4]), "+f"(d[5]), "+f"(d[6]), "+f"(d[7]), "+f"(d[8]), "+f"(d[9]), "+f"(d[10]), "+f"(d[11]), "+f"(d[12]), "+f"(d[13]), "+f"(d[14]), "+f"(d[15]), "+f"(d[16]), "+f"(d[17]), "+f"(d[18]), "+f"(d[19]), "+f"(d[20]), "+f"(d[21]), "+f"(d[22]), "+f"(d[23]), "+f"(d[24]), "+f"(d[25]), "+f"(d[26]), "+f"(d[27]), "+f"(d[28]), "+f"(d[29]), "+f"(d[30]), "+f"(d[31])
    : "r"(a0), "r"(a1), "r"(a2), "r"(a3), "l"(db));
}
__device__ __forceinline__ void wgmma_rs_n32(float* d, uint32_t a0, uint32_t a1, uint32_t a2, uint32_t a3, uint64_t db) {
  asm volatile("wgmma.mma_async.sync.aligned.m64n32k16.f32.bf16.bf16 {%0, %1, %2, %3, %4, %5, %6, %7, %8, %9, %10, %11, %12, %13, %14, %15}, {%16, %17, %18, %19}, %20, 1, 1, 1, 0;"
    : "+f"(d[0]), "+f"(d[1]), "+f"(d[2]), "+f"(d[3]), "+f"(d[4]), "+f"(d[5]), "+f"(d[6]), "+f"(d[7]), "+f"(d[8]), "+f"(d[9]), "+f"(d[10]), "+f"(d[11]), "+f"(d[12]), "+f"(d[13]), "+f"(d[14]), "+f"(d[15])
    : "r"(a0), "r"(a1), "r"(a2), "r"(a3), "l"(db));
}
__device__ __forceinline__ void wgmma_ss_n80_t10(float* d, uint64_t da, uint64_t db) {
  asm volatile("wgmma.mma_async.sync.aligned.m64n80k16.f32.bf16.bf16 {%0, %1, %2, %3, %4, %5, %6, %7, %8, %9, %10, %11, %12, %13, %14, %15, %16, %17, %18, %19, %20, %21, %22, %23, %24, %25, %26, %27, %28, %29, %30, %31, %32, %33, %34, %35, %36, %37, %38, %39}, %40, %41, 1, 1, 1, 1, 0;"
    : "+f"(d[0]), "+f"(d[1]), "+f"(d[2]), "+f"(d[3]), "+f"(d[4]), "+f"(d[5]), "+f"(d[6]), "+f"(d[7]), "+f"(d[8]), "+f"(d[9]), "+f"(d[10]), "+f"(d[11]), "+f"(d[12]), "+f"(d[13]), "+f"(d[14]), "+f"(d[15]), "+f"(d[16]), "+f"(d[17]), "+f"(d[18]), "+f"(d[19]), "+f"(d[20]), "+f"(d[21]), "+f"(d[22]), "+f"(d[23]), "+f"(d[24]), "+f"(d[25]), "+f"(d[26]), "+f"(d[27]), "+f"(d[28]), "+f"(d[29]), "+f"(d[30]), "+f"(d[31]), "+f"(d[32]), "+f"(d[33]), "+f"(d[34]), "+f"(d[35]), "+f"(d[36]), "+f"(d[37]), "+f"(d[38]), "+f"(d[39])
    : "l"(da), "l"(db));
}
__device__ __forceinline__ void wgmma_ss_n152_t10(float* d, uint64_t da, uint64_t db) {
  asm volatile("wgmma.mma_async.sync.aligned.m64n152k16.f32.bf16.bf16 {%0, %1, %2, %3, %4, %5, %6, %7, %8, %9, %10, %11, %12, %13, %14, %15, %16, %17, %18, %19, %20, %21, %22, %23, %24, %25, %26, %27, %28, %29, %30, %31, %32, %33, %34, %35, %36, %37, %38, %39, %40, %41, %42, %43, %44, %45, %46, %47, %48, %49, %50, %51, %52, %53, %54, %55, %56, %57, %58, %59, %60, %61, %62, %63, %64, %65, %66, %67, %68, %69, %70, %71, %72, %73, %74, %75}, %76, %77, 1, 1, 1, 1, 0;"
    : "+f"(d[0]), "+f"(d[1]), "+f"(d[2]), "+f"(d[3]), "+f"(d[4]), "+f"(d[5]), "+f"(d[6]), "+f"(d[7]), "+f"(d[8]), "+f"(d[9]), "+f"(d[10]), "+f"(d[11]), "+f"(d[12]), "+f"(d[13]), "+f"(d[14]), "+f"(d[15]), "+f"(d[16]), "+f"(d[17]), "+f"(d[18]), "+f"(d[19]), "+f"(d[20]), "+f"(d[21]), "+f"(d[22]), "+f"(d[23]), "+f"(d[24]), "+f"(d[25]), "+f"(d[26]), "+f"(d[27]), "+f"(d[28]), "+f"(d[29]), "+f"(d[30]), "+f"(d[31]), "+f"(d[32]), "+f"(d[33]), "+f"(d[34]), "+f"(d[35]), "+f"(d[36]), "+f"(d[37]), "+f"(d[38]), "+f"(d[39]), "+f"(d[40]), "+f"(d[41]), "+f"(d[42]), "+f"(d[43]), "+f"(d[44]), "+f"(d[45]), "+f"(d[46]), "+f"(d[47]), "+f"(d[48]), "+f"(d[49]), "+f"(d[50]), "+f"(d[51]), "+f"(d[52]), "+f"(d[53]), "+f"(d[54]), "+f"(d[55]), "+f"(d[56]), "+f"(d[57]), "+f"(d[58]), "+f"(d[59]), "+f"(d[60]), "+f"(d[61]), "+f"(d[62]), "+f"(d[63]), "+f"(d[64]), "+f"(d[65]), "+f"(d[66]), "+f"(d[67]), "+f"(d[68]), "+f"(d[69]), "+f"(d[70]), "+f"(d[71]), "+f"(d[72]), "+f"(d[73]), "+f"(d[74]), "+f"(d[75])
    : "l"(da), "l"(db));
}

template <int ST> __device__ __forceinline__ void conv_load(uint32_t (&a)[16], uint32_t pa, uint32_t zero) {
  constexpr int U = 512 * (ST / 2) + 64 * (ST % 2);
  uint32_t p[9];
#pragma unroll
  for (int i = 0; i < 9; i++) p[i] = lds32(pa + (U + 8 * i - 8) * 4);
#pragma unroll
  for (int r = 0; r < 4; r++) {
    a[4 * r + 0] = p[2 * r + 1];
    a[4 * r + 1] = p[2 * r + 2];
    a[4 * r + 2] = r == 0 ? p[0] : (p[2 * r] ^ zero);
    a[4 * r + 3] = p[2 * r + 1] ^ zero;
  }
}
__device__ __forceinline__ void conv_fa(uint32_t (&a)[16]) {
#pragma unroll
  for (int i = 0; i < 16; i++) asm volatile("" : "+r"(a[i])::"memory");
  wg_fence();
}
template <int N> __device__ __forceinline__ void conv_g(float* acc, const uint32_t (&a)[16], uint64_t db) {
#pragma unroll
  for (int r = 0; r < 4; r++) {
    if (N == 64) wgmma_rs_n64(acc, a[4 * r], a[4 * r + 1], a[4 * r + 2], a[4 * r + 3], db - (uint64_t)r);
    else wgmma_rs_n32(acc, a[4 * r], a[4 * r + 1], a[4 * r + 2], a[4 * r + 3], db - (uint64_t)r);
  }
}
__device__ __forceinline__ void red_add(float* y, uint32_t a) {
  const float2 v = lds64f(a);
  const uint32_t u0 = __float_as_uint(v.x), u1 = __float_as_uint(v.y);
  y[0] += blo(u0); y[1] += bhi(u0); y[2] += blo(u1); y[3] += bhi(u1);
}
__device__ __forceinline__ void conv_channel(uint32_t sb, int slot, int wg, int ch, uint32_t zero, float dcoef, const CUtensorMap* ym, long long t_start) {
  const int tid = threadIdx.x & 127, w = __shfl_sync(0xffffffffu, tid >> 5, 0), lane = tid & 31, g = lane >> 2, t = lane & 3;
  const uint32_t P = sb + OFF_P + slot * PBYTES, X = sb + OFF_XC + slot * XBYTES + 128;
  const uint32_t pa = P + (P2 ? 128 : 64) + (128 * w + g - 2 * t) * (P2 ? 8 : 4);
  const uint64_t db0 = mkdesc(X, XLBO, 128, 0);
  const float zf = __uint_as_float(zero);
  float acc[64];
#pragma unroll
  for (int i = 0; i < 64; i++) acc[i] = 0.f;
  uint32_t a0[16], a1[16];
  conv_load<6>(a0, pa, zero);
  mbar_wait_u(BAR(B_XC + slot), 0);
  if (CTOK && (slot == 1 || slot == 2)) mbar_wait_u(BAR(B_TA + slot - 1), 0);
  PROF0(8 + 4 * slot);
  conv_fa(a0); conv_g<32>(acc + 48, a0, db0); wg_commit(); conv_load<7>(a1, pa, zero);
  conv_fa(a1); conv_g<32>(acc + 48, a1, db0 - 4); wg_commit(); wg_wait<1>(); conv_load<0>(a0, pa, zero);
  conv_fa(a0); conv_g<64>(acc, a0, db0); wg_commit(); wg_wait<1>();
  conv_load<1>(a1, pa, zero);
#pragma unroll
  for (int i = 48; i < 64; i++) acc[i] += zf;
  wg_fence(); conv_g<64>(acc + 32, a0, db0 + 64); wg_commit();
  conv_fa(a1); conv_g<64>(acc, a1, db0 - 4); conv_g<64>(acc + 32, a1, db0 + 60); wg_commit(); wg_wait<1>();
  mbar_arrive_if(BAR(B_TA), tid == 0 && slot == 0);
  conv_load<2>(a0, pa, zero);
  conv_fa(a0); conv_g<64>(acc + 32, a0, db0 + 32); wg_commit(); wg_wait<1>();
  conv_load<3>(a1, pa, zero);
#pragma unroll
  for (int i = 16; i < 32; i++) acc[i] += zf;
  wg_fence(); conv_g<32>(acc + 16, a0, db0); wg_commit();
  conv_fa(a1); conv_g<64>(acc + 32, a1, db0 + 28); conv_g<32>(acc + 16, a1, db0 - 4); wg_commit(); wg_wait<1>();
  conv_load<4>(a0, pa, zero);
  mbar_arrive_if(BAR(B_TA + 1), tid == 0 && slot == 0);
  conv_fa(a0); conv_g<64>(acc + 32, a0, db0); wg_commit(); wg_wait<1>();
  conv_load<5>(a1, pa, zero);
  conv_fa(a1); conv_g<64>(acc + 32, a1, db0 - 4); wg_commit(); wg_wait<0>();
  PROF0(9 + 4 * slot);
  constexpr int RS = RED16 ? 256 : 512;
  const uint32_t R = sb + OFF_RED + wg * RBYTES + lane * (RS / 32);
  float y[16];
#pragma unroll
  for (int ww = 0; ww < 4; ww++) {
    if (w == ww) {
#pragma unroll
      for (int j = 0; j < 16 - ww; j++) {
        const int jo = j + ww, ow = jo >> 2, jj = jo & 3;
        if (ow == ww) { y[4 * jj] = acc[4 * j]; y[4 * jj + 1] = acc[4 * j + 1]; y[4 * jj + 2] = acc[4 * j + 2]; y[4 * jj + 3] = acc[4 * j + 3]; }
        else {
          const int sidx = ww < ow ? ww : ww - 1;
          const int idx = ow > 0 ? 6 + (ow - 1) * 12 + sidx * 4 + jj : (ww == 1 ? jj - 1 : (ww == 2 ? 3 + jj - 2 : 5));
          sts64u(R + idx * RS, pack2(acc[4 * j], acc[4 * j + 1]), pack2(acc[4 * j + 2], acc[4 * j + 3]));
        }
      }
    }
  }
  bar_sync(1 + wg, 128);
  if (w == 0) {
#pragma unroll
    for (int idx = 0; idx < 6; idx++) red_add(y + 4 * (idx < 3 ? idx + 1 : (idx < 5 ? idx - 1 : 3)), R + idx * RS);
  } else {
    const uint32_t Rw = R + (6 + (w - 1) * 12) * RS;
#pragma unroll
    for (int idx = 0; idx < 12; idx++) red_add(y + 4 * (idx & 3), Rw + idx * RS);
  }
#pragma unroll
  for (int h = 0; h < 2; h++) {
    const float* yy = y + 8 * h;
    stsm4t(P + (32 * w + 16 * h + 8 * (lane >> 4) + (lane & 7)) * 32 + ((lane >> 3) & 1) * 16,
           pack2(yy[0], yy[1]), pack2(yy[2], yy[3]), pack2(yy[4], yy[5]), pack2(yy[6], yy[7]));
  }
  fence_async_smem();
  bar_sync(1 + wg, 128);
  if (w == 0 && elect_one()) { tma_store3(ym, P, 0, ch, 0); bulk_commit(); }
  PROF0(10 + 4 * slot);
}
__device__ __forceinline__ void conv_build(uint32_t sb, int slot, uint2 (&kr)[4], const uint32_t (&pv)[4], float dfold) {
  const int tid = threadIdx.x & 127, lane = tid & 31;
  if (DFOLD && tid == 0) kr[0].x = (kr[0].x & 0xffff0000u) | (pack2(blo(kr[0].x) + dfold, 0.f) & 0xffffu);
  const uint32_t P = sb + OFF_P + slot * PBYTES + 64;
#pragma unroll
  for (int i = 0; i < 4; i++) {
    uint32_t prev = __shfl_up_sync(0xffffffffu, kr[i].y, 1);
    if (lane == 0) prev = pv[i];
    sts128u(P + (tid + 128 * i) * 16, __byte_perm(kr[i].x, prev, 0x7610), __byte_perm(kr[i].x, 0, 0x1032), __byte_perm(kr[i].y, kr[i].x, 0x7610), __byte_perm(kr[i].y, 0, 0x1032));
  }
  if (tid < 4) sts128u(P - 64 + tid * 16, 0, 0, 0, 0);
  if (tid < 16) sts128u(sb + OFF_XC + slot * XBYTES + (tid >> 3) * XLBO + (tid & 7) * 16, 0, 0, 0, 0);
}
__device__ __forceinline__ void conv_fetch(const __nv_bfloat16* ssm, int ch, uint2 (&kr)[4], uint32_t (&pv)[4]) {
  const int tid = threadIdx.x & 127, lane = tid & 31;
  const char* p = (const char*)(ssm + (size_t)ch * S);
#pragma unroll
  for (int i = 0; i < 4; i++) {
    const int c = tid + 128 * i;
    asm volatile("ld.global.nc.v2.u32 {%0,%1}, [%2];" : "=r"(kr[i].x), "=r"(kr[i].y) : "l"(p + c * 8));
    pv[i] = 0;
    if (lane == 0 && c > 0) asm volatile("ld.global.nc.u32 %0, [%1];" : "=r"(pv[i]) : "l"(p + c * 8 - 4));
  }
}

struct Cur {
  uint32_t slot, par;
  template <int N> __device__ __forceinline__ void adv(uint32_t n) { slot += n; if (slot >= N) { slot -= N; par ^= 1; } }
};

__host__ __device__ constexpr int joint_of(int ph) { return ph == 1 ? JOINT1 : (ph == 2 ? JOINT2 : JOINT3); }
__host__ __device__ constexpr int unit_pos(int ph, int w, int u) {
  const int nwg = ph == 3 ? 3 : 2, j = joint_of(ph);
  return u < j ? u * nwg + w : j * nwg + w * (5 - j) + u - j;
}
__host__ __device__ constexpr uint32_t unit_slots(int ph, int w) {
  uint32_t m = 0;
  for (int u = 0; u < 5; u++) { const int q = 10 * (ph - 1) + unit_pos(ph, w, u); m |= (uint32_t)(q % NWU | ((q / NWU) & 1) << 3) << (4 * u); }
  return m;
}
__host__ __device__ constexpr uint64_t unit_order(int ph) {
  uint64_t m = 0;
  for (int w = 0; w < (ph == 3 ? 3 : 2); w++)
    for (int u = 0; u < 5; u++) m |= (uint64_t)(w * 5 + u) << (4 * unit_pos(ph, w, u));
  return m;
}
constexpr uint64_t D128 = ((uint64_t)1 << 62) | ((uint64_t)64 << 32), D64 = ((uint64_t)2 << 62) | ((uint64_t)32 << 32);
constexpr uint64_t DA0 = D128 | ((SB + OFF_W) >> 4), DB0 = D128 | (1 << 16) | ((SB + OFF_X) >> 4), DBS = D64 | (1 << 16) | ((SB + OFF_X) >> 4);
template <int NR> __device__ __forceinline__ void mma4(float* acc, uint64_t da, uint64_t db, uint64_t db2) {
  if (NR == 80) {
    wgmma_ss_n80_t10(acc, da, db); wgmma_ss_n80_t10(acc, da + 128, db + 2);
    wgmma_ss_n80_t10(acc, da + 256, db2); wgmma_ss_n80_t10(acc, da + 384, db2 + 2);
  } else {
    wgmma_ss_n152_t10(acc, da, db); wgmma_ss_n152_t10(acc, da + 128, db + 2);
    wgmma_ss_n152_t10(acc, da + 256, db2); wgmma_ss_n152_t10(acc, da + 384, db2 + 2);
  }
}
template <int PH> __device__ __forceinline__ void mma_g12(float* acc, int wg, bool leader, long long t_start, int pb) {
  constexpr uint32_t sb = SB;
  constexpr uint32_t s0 = unit_slots(PH, 0), s1 = unit_slots(PH, 1);
  const uint32_t sl = wg == 0 ? s0 : s1, xcnt = wg == 0 ? 2 : 1;
#pragma unroll
  for (int u = 0; u < 5; u++) {
    if (u == joint_of(PH) && wg == 1) {
      if (u > 0) { wg_wait<0>(); mbar_arrive_if(BAR(B_EW) + 8 * ((sl >> (4 * u - 4)) & 7), leader); }
      mbar_wait_u(BAR(B_K1 + PH - 1), 0);
    }
    const uint32_t ws = (sl >> (4 * u)) & 7;
    mbar_wait2(BAR(B_FW) + 8 * ws, (sl >> (4 * u + 3)) & 1, BAR(B_FX + u), PH - 1);
    const uint64_t da = DA0 + ws * (WU / 16);
    constexpr uint64_t xo = XS / 16;
    wg_fence();
    if (PH == 2 && u == 1) mma4<80>(acc, da, DBS + u * xo, DBS + u * xo + 320); else mma4<80>(acc, da, DB0 + u * xo, DB0 + u * xo + 4);
    if (PH == 2 && u == 3) mma4<80>(acc, da + 512, DBS + u * xo + 640, DBS + u * xo + 960); else mma4<80>(acc, da + 512, DB0 + u * xo + 640, DB0 + u * xo + 644);
    wg_commit();
    if (u == 4) mbar_arrive_if(BAR(B_K1 + PH - 1), leader && wg == 0);
    if (u > 0) {
      wg_wait<1>();
      mbar_arrive_if(BAR(B_EW) + 8 * ((sl >> (4 * u - 4)) & 7), leader && !(u == joint_of(PH) && wg == 1));
      mbar_arrive_n_if(BAR(B_EX + u - 1), xcnt, leader);
    }
  }
  wg_wait<0>();
  mbar_arrive_if(BAR(B_EW) + 8 * ((sl >> 16) & 7), leader);
  mbar_arrive_n_if(BAR(B_EX + 4), xcnt, leader);
}
__device__ __forceinline__ void mma_g3(float* acc, int wg, bool leader, long long t_start, int pb) {
  constexpr uint32_t sb = SB;
  uint32_t sl = wg == 0 ? unit_slots(3, 0) : (wg == 1 ? unit_slots(3, 1) : unit_slots(3, 2));
  uint32_t xs = 0, xp = 0, pw = 0, px = 0;
#pragma unroll 1
  for (int u = 0; u < 5; u++) {
    const uint32_t ws = sl & 7;
    const uint64_t da = DA0 + ws * (WU / 16);
#pragma unroll
    for (int h = 0; h < 2; h++) {
      const bool pause = h == 1 && u == 2 && wg > 0;
      if (h == 1 && pause) {
        wg_wait<0>();
        mbar_arrive_if(BAR(B_EX) + 8 * px, leader);
        mbar_wait_u(BAR(B_K3 + wg - 1), 0);
        if (PAUSE2 && wg == 2) mbar_wait_u(BAR(B_GC), 0);
      }
      if (h == 0) mbar_wait2(BAR(B_FW) + 8 * ws, (sl >> 3) & 1, BAR(B_FX) + 8 * xs, xp); else mbar_wait1(BAR(B_FX) + 8 * xs, xp);
      const uint64_t db = DB0 + xs * (XS / 16);
      wg_fence();
      mma4<152>(acc, da + 512 * h, db, db + 4);
      wg_commit();
      if (h == 1) mbar_arrive_if(BAR(B_K3 + (wg & 1)), leader && wg < 2 && u == 4);
      wg_wait<1>();
      if (h == 0) mbar_arrive_if(BAR(B_EW) + 8 * pw, leader && u > 0);
      mbar_arrive_if(BAR(B_EX) + 8 * px, leader && (h == 1 ? !pause : u > 0));
      px = xs;
      if (++xs == 5) { xs = 0; xp = 1; }
    }
    pw = ws; sl >>= 4;
  }
  wg_wait<0>();
  mbar_arrive_if(BAR(B_EW) + 8 * pw, leader);
  mbar_arrive_if(BAR(B_EX) + 8 * px, leader);
}
__device__ __forceinline__ void mma_g4(float* acc, int wg, uint32_t pos, bool leader, long long t_start, int pb) {
  constexpr uint32_t sb = SB;
  const uint32_t xcnt = wg == 0 ? 2 : 1;
  const uint64_t da0 = DA0 + wg * 512;
  Cur w{pos % NWU, (pos / NWU) & 1}, x{0, 0};
  uint32_t pw = 0, px = 0;
#pragma unroll 1
  for (int c = 0; c < 27; c++) {
    mbar_wait2(BAR(B_FW) + 8 * w.slot, w.par, BAR(B_FX) + 8 * x.slot, x.par);
    const uint64_t db = DB0 + x.slot * (XS / 16) + (c & 1) * 640;
    wg_fence();
    mma4<80>(acc, da0 + w.slot * (WU / 16), db, db + 4);
    wg_commit();
    wg_wait<1>();
    mbar_arrive_if(BAR(B_E4) + 8 * pw, leader && c > 0);
    mbar_arrive_n_if(BAR(B_EX) + 8 * px, xcnt, leader && c > 0 && !(c & 1));
    pw = w.slot; px = x.slot;
    w.adv<NWU>(1); x.adv<5>(c & 1);
  }
  wg_wait<0>();
}

__device__ __forceinline__ void w_unit(Cur& s, const CUtensorMap* tm, int f, int k) {
  constexpr uint32_t sb = SB;
  mbar_wait(BAR(B_EW) + 8 * s.slot, s.par ^ 1);
  mbar_expect(BAR(B_FW) + 8 * s.slot, WU);
  tma_load(sb + OFF_W + s.slot * WU, tm, BAR(B_FW) + 8 * s.slot, (EXPT & 2) ? 0 : f, k);
  s.adv<NWU>(1);
}

__device__ __forceinline__ uint32_t tile_addr(uint32_t st) {
  const int lane = threadIdx.x & 31, w = (threadIdx.x >> 5) & 3;
  return st + (8 * (lane >> 4) + (lane & 7)) * 128 + (((2 * w + ((lane >> 3) & 1)) ^ (lane & 7)) << 4);
}
template <int NJ> __device__ __forceinline__ void stage_tile(uint32_t st, const uint32_t* pk) {
  const uint32_t a = tile_addr(st);
#pragma unroll
  for (int j = 0; j + 1 < NJ; j += 2) stsm4t(a + j * 1024, pk[2 * j], pk[2 * j + 1], pk[2 * j + 2], pk[2 * j + 3]);
  if (NJ & 1) stsm2t(a + (NJ - 1) * 1024 - ((threadIdx.x & 31) >> 4) * 1024, pk[2 * NJ - 2], pk[2 * NJ - 1]);
}
template <int UNR> __device__ __forceinline__ void row_stats(uint32_t tile, uint32_t dst, int r) {
  float s1 = 0.f, s2 = 0.f;
#pragma unroll UNR
  for (int i = 0; i < 8; i++) {
    const float4 v = lds128f(tile + r * 128 + (((i + r) & 7) << 4));
    const uint32_t u[4] = {__float_as_uint(v.x), __float_as_uint(v.y), __float_as_uint(v.z), __float_as_uint(v.w)};
#pragma unroll
    for (int m = 0; m < 4; m++) { const float x0 = blo(u[m]), x1 = bhi(u[m]); s1 += x0 + x1; s2 = fmaf(x0, x0, fmaf(x1, x1, s2)); }
  }
  sts64f(dst + r * 8, s1, s2);
}
__device__ __forceinline__ float2 gather_stats(int which, int row) {
  float s1 = 0.f, s2 = 0.f;
#pragma unroll
  for (int i = 0; i < 10; i++) { const float2 v = ldcg64f(&g_st[which][i][row]); s1 += v.x; s2 += v.y; }
  const float m = s1 * (1.f / D);
  return make_float2(m, fmaxf(s2 * (1.f / D) - m * m, 0.f));
}
__global__ void __launch_bounds__(NTHR, 1) fused_kernel(const __grid_constant__ Params p, uint32_t zero) {
  extern __shared__ __align__(1024) char smem[];
  constexpr uint32_t sb = SB;
  if (s2u(smem) != SB) return;
  const int b = blockIdx.x, tid = threadIdx.x;
  const int warp = __shfl_sync(0xffffffffu, tid >> 5, 0), lane = tid & 31, wg = warp >> 2;
  const int ft = MAP2 == 1 ? (b >> 1) % 5 : (MAP2 == 2 ? (b < 120 ? (b % 15) / 3 : (b - 120) >> 1) : b % 5), rt = MAP2 == 1 ? 2 * (b / 10) + (b & 1) : (MAP2 == 2 ? (b < 120 ? 3 * (b / 15) + b % 3 : 24 + (b & 1)) : b / 5);
  const int pb3 = b < 90 ? b / 45 : 2, pr3 = b < 90 ? 5 : 4, ib3 = b - 45 * pb3;
  const int ft3 = (ib3 / (3 * pr3)) * 3 + ib3 % 3, rt3 = 5 * pb3 + (ib3 % (3 * pr3)) / 3;
  const bool has3 = b < 126, hasC = b < 128;
  const int r0 = rt * 80, r3 = rt3 * 152;

  if (tid < 320) {
    const int o = lane & 7, gi = lane >> 3, c0 = 64 * (b % 10) + 8 * o, rb = 160 * (b / 10) + 16 * warp + 4 * gi;
    if (rb < S) {
      uint4 kk[7], vv[4], sw[4];
#pragma unroll
      for (int i = 3; i < 7; i++) kk[i] = ldg128c(p.k + (size_t)(rb + i - 3) * D + c0);
#pragma unroll
      for (int i = 0; i < 4; i++) vv[i] = ldg128(p.v + (size_t)(rb + i) * D + c0);
#pragma unroll
      for (int i = 0; i < 3; i++) { kk[i] = make_uint4(0, 0, 0, 0); if (rb > 0) kk[i] = ldg128c(p.k + (size_t)(rb + i - 3) * D + c0); }
#pragma unroll
      for (int i = 0; i < 4; i++) sw[i] = ldg128c(p.shk + (size_t)c0 * 4 + 8 * i);
      const uint32_t dst = sb + OFF_KV + (gi >> 1) * 1280 + o * 160 + warp * 16 + (gi & 1) * 8;
#pragma unroll
      for (int j = 0; j < 8; j++) {
        const uint32_t s01 = ((const uint32_t*)sw)[2 * j], s23 = ((const uint32_t*)sw)[2 * j + 1];
        const float w0 = blo(s01), w1 = bhi(s01), w2 = blo(s23), w3 = bhi(s23);
        float kf[7], ov[4];
#pragma unroll
        for (int i = 0; i < 7; i++) { const uint32_t u = ((const uint32_t*)&kk[i])[j >> 1]; kf[i] = (j & 1) ? bhi(u) : blo(u); }
#pragma unroll
        for (int i = 0; i < 4; i++) {
          const uint32_t u = ((const uint32_t*)&vv[i])[j >> 1];
          ov[i] = fmaf(w0, kf[i + 3], fmaf(w1, kf[i + 2], fmaf(w2, kf[i + 1], w3 * kf[i]))) * ((j & 1) ? bhi(u) : blo(u));
        }
        sts64u(dst + j * 2560, pack2(ov[0], ov[1]), pack2(ov[2], ov[3]));
        if (KVSPLIT && j == 3) { fence_async_smem(); bar_arrive(9, 352); }
      }
      fence_async_smem();
    } else if (KVSPLIT) bar_arrive(9, 352);
  } else if (warp == 12) {
    if (elect_one()) {
#pragma unroll
    for (int i = 0; i < NBAR; i++) mbar_init(BAR(i), ((i >= B_EX && i < B_EX + 6) || i == B_CD || i == B_QD) ? 3 : (i == B_SR ? 4 : ((i >= B_E4 && i < B_E4 + 6) ? 2 : 1)));
    asm volatile("fence.mbarrier_init.release.cluster;" ::: "memory");
    fence_async_smem();
    }
    if (KVSPLIT) {
      bar_sync(9, 352);
      if (elect_one()) tma_store4(&p.kv, sb + OFF_KV, (b / 10) * 80, (b % 10) * 8, 0, 0);
    }
  }

  if (wg == 3) {
    const unsigned e1 = *(volatile unsigned*)&g_epoch + 1;
    if (tid == 511) sts32f(sb + OFF_EP, __uint_as_float(e1));
    __syncthreads();
    asm volatile("setmaxnreg.dec.sync.aligned.u32 56;");
    if (warp == 12) {
      if (elect_one()) {
        PROFT(0);
        if (!KVSPLIT) tma_store4(&p.kv, sb + OFF_KV, (b / 10) * 80, (b % 10) * 8, 0, 0);
        tma_store4(&p.kv, sb + OFF_KV + 4 * 2560, (b / 10) * 80, (b % 10) * 8, 0, 4);
        bulk_commit();
        bulk_wait0();
        red_cnt(CNT(C_KV + b % 10, 0));
        PROFT(1);
        mbar_wait(BAR(B_DEP), 0);
        PROFT(2);
        if (hasC) {
#pragma unroll 1
          for (int j = 0; j < 5; j++) {
            const uint32_t fb = BAR(B_XC + j), dst = sb + OFF_XC + j * XBYTES + 128;
            mbar_expect(fb, 4096);
            bulk_load(dst, g_kvT + (size_t)(b * 5 + j) * S, 2048, fb);
            bulk_load(dst + XLBO, g_kvT + (size_t)(b * 5 + j) * S + 1024, 2048, fb);
          }
        }
        mbar_expect(BAR(B_QT), 20480);
        tma_load(sb + OFF_QT, &p.q80, BAR(B_QT), ft * 64, r0);
        tma_load(sb + OFF_QT + 10240, &p.q80, BAR(B_QT), ft * 64 + 320, r0);
        if (hasC) { mbar_wait(BAR(B_CD), 0); if (PFMODE == 3) mbar_wait(BAR(B_PF), 0); }
        mbar_expect(BAR(B_YT), 20480);
        mbar_wait(BAR(B_DEP + 1), 0);
        bulk_load(sb + OFF_YT, g_yB + ((size_t)rt * D + ft * 64) * 80, 10240, BAR(B_YT));
        bulk_load(sb + OFF_YT + 10240, g_yB + ((size_t)rt * D + ft * 64 + 320) * 80, 10240, BAR(B_YT));
        PROFT(3);
#pragma unroll
        for (int u = 0; u < 5; u++) mbar_expect(BAR(B_FX + u), XS);
        mbar_wait(BAR(B_DEP + 2), 0);
#pragma unroll
        for (int u = 0; u < 5; u++) { if (u >= XWIN) mbar_wait(BAR(B_FX + u - XWIN), 0); tma_load3(sb + OFF_X + u * XS, &p.h2, BAR(B_FX + u), 0, r0, 2 * u); }
        PROFT(4);
#pragma unroll
        for (int u = 0; u < 5; u++) { mbar_wait(BAR(B_EX + u), 0); mbar_expect(BAR(B_FX + u), XS); }
#pragma unroll
        for (int c = 0; c < 10; c++) {
          if (c == 0 || c == 5) { mbar_wait(BAR(B_DEP + 3 + c / 5), 0); PROFT(c == 0 ? 5 : 27); }
          if (!(c & 1) && c / 2 >= XWIN) mbar_wait(BAR(B_FX + c / 2 - XWIN), 1);
          const int d = c < 5 ? 1 : 2;
          const uint32_t dst = sb + OFF_X + c * 10240;
          if (c == 2 || c == 7) {
            tma_load(dst, &p.h1n, BAR(B_FX + c / 2), c * 64, r0 - d);
            tma_load(dst + 5120, &p.h1n, BAR(B_FX + c / 2), c * 64 + 32, r0 + d);
          } else {
            tma_load(dst, &p.h1, BAR(B_FX + c / 2), c * 64, (c < 2 || c == 5 || c == 6) ? r0 - d : r0 + d);
          }
        }
        if (has3) {
#pragma unroll 1
          for (int c = 0; c < 10; c++) {
            const int j = c < 5 ? c : c - 5;
            mbar_wait(BAR(B_EX) + 8 * j, c < 5);
            mbar_expect(BAR(B_FX) + 8 * j, 152 * 128);
            if (j == 0) { mbar_wait(BAR(B_DEP + 5) + (c ? 8 : 0), 0); PROFT(c == 0 ? 6 : 11); }
            if (c >= XWIN && c < 5) mbar_wait(BAR(B_FX) + 8 * (c - XWIN), 0);
            tma_load(sb + OFF_X + j * XS, &p.x1l, BAR(B_FX) + 8 * j, c * 64, r3);
          }
        }
        Cur xs{0, 0};
#pragma unroll 1
        for (int u = 0; u < 14; u++) {
          mbar_wait(BAR(B_EX) + 8 * xs.slot, xs.par ^ 1);
          mbar_expect(BAR(B_FX) + 8 * xs.slot, XS);
          if ((GSYNC & 8) && u == XEARLY) mbar_wait(BAR(B_DEP + 10), 0);
          if (u == 0 || u == 4 || u == 9) { mbar_wait(BAR(B_DEP + 7) + (u == 0 ? 0 : (u == 4 ? 8 : 16)), 0); PROFT(u == 0 ? 7 : (u == 4 ? 15 : 19)); }
          tma_load3(sb + OFF_X + xs.slot * XS, &p.hl2, BAR(B_FX) + 8 * xs.slot, 0, r0, 2 * u);
          if (u == 2) mbar_arrive(BAR(B_XI));
          if (u == 13 && b == 0) *(volatile unsigned*)&g_epoch = e1;
          xs.adv<5>(1);
        }
      }
    } else if (warp == 15) {
      const int g1lo = max(rt - 1, 0), g1hi = min(rt + 1, 25), g2lo = r3 / 80, g2hi = min(25, (r3 + 151) / 80), g3lo = r0 / 152, g3hi = min(13, (r0 + 79) / 152);
#pragma unroll 1
      for (int d = 0; d < 10; d++) {
        const unsigned* c; unsigned n;
        if (d >= 5 && d < 7 && !has3) continue;
        if (((LSG >> d) & 1) && (d < 7 || has3)) mbar_wait(BAR(B_LS - 2) + 8 * d, 0);
        if (d == 0) { if (!hasC) { if (lane == 0) mbar_arrive(BAR(B_DEP)); continue; } c = CNT(C_KV + (5 * b + (lane ? 4 : 0)) / 64, 0); n = 13; }
        else if (d == 1) { c = CNT(C_Y + ft + (lane ? 5 : 0), 0); n = 64; if (hasC) mbar_wait(BAR(B_CD), 0); }
        else if (d == 2) { c = CNT(C_T + rt, 0); n = 10; }
        else if (d < 5) { c = CNT(C_G1 + 26 * (d - 3) + min(g1lo + lane, g1hi), 0); n = 5; }
        else if (d < 7) { c = CNT(C_G2 + 26 * (d - 5) + min(g2lo + lane, g2hi), 0); n = 5; }
        else { c = CNT(C_G3 + d - 7, (d == 7 || (GSYNC & (d == 8 ? 16 : 32))) ? min(lane, 13) : min(g3lo + lane, g3hi)); n = 9; }
        if (d == 7) {
          const unsigned own = (1u << g3lo) | (1u << g3hi);
          bool sent = false;
          unsigned v = 0;
#pragma unroll 1
          for (int it = 0; it < (1 << 20); it++) {
            v = ld_cnt(lane == 14 ? CNT(C_G3, 14) : c);
            const unsigned m = __ballot_sync(0xffffffffu, lane == 14 || (int)(v - e1 * n) >= 0);
            if (!sent && (m & own) == own) { sent = true; if (lane == 0) mbar_arrive(BAR(B_DEP + 7)); }
            if (m == 0xffffffffu) break;
          }
          if (TALIGN) {
            const unsigned t0 = __shfl_sync(0xffffffffu, v, 14) + TALIGN;
            for (int it = 0; it < 200 && (int)(gtime32() - t0) < 0; it++) { }
          }
          if (lane == 0) mbar_arrive(BAR(B_DEP + 10));
          continue;
        }
        wait_cnt_w(c, e1 * n);
        if (lane == 0) mbar_arrive(BAR(B_DEP) + 8 * d);
      }
    } else if (warp == 13) {
      mbar_wait(BAR(B_QT), 0);
#pragma unroll 1
      for (int n = lane; n < 160; n += 32) { const int hf = n >= 80; row_stats<8>(sb + OFF_QT + hf * 10240, sb + OFF_PQ + hf * 640, n - 80 * hf); }
      fence_async_smem();
      __syncwarp();
      if (elect_one()) {
        mbar_arrive(BAR(B_QD));
        bulk_store(&g_st[0][ft][r0], sb + OFF_PQ, 640); bulk_store(&g_st[0][ft + 5][r0], sb + OFF_PQ + 640, 640);
        bulk_commit(); bulk_wait0(); red_cnt(CNT(C_SQ + rt, 0)); PROFT(23);
      }
      __syncwarp();
      if (has3) {
        if (LSG) mbar_wait(BAR(B_LS + 4), 0);
        wait_cnt_w(CNT(C_SX + min(r3 / 80 + lane, min(25, (r3 + 151) / 80)), 0), e1 * 10);
#pragma unroll 1
        for (int r = lane; r < 152; r += 32) {
          const float2 s = gather_stats(2, r3 + r);
          const float rs = 0.5f * rsqrtf(s.y + EPS);
          sts64f(sb + OFF_RP3 + r * 8, rs, -s.x * rs);
        }
        __syncwarp();
        if (elect_one()) {
          mbar_arrive(BAR(B_RP3)); PROFT(30);
#pragma unroll 1
          for (int w = 0; w < 3; w++) {
            const uint32_t src = sb + OFF_ST;
            if (SPLIT0 && w == 0) { mbar_wait(BAR(B_SG + 3), 0); tma_store(&p.hs, src, ft3 * 64, r3); }
            mbar_wait(BAR(B_SG) + 8 * w, 0);
            if (w == GATE) mbar_wait(BAR(B_XI), 0);
            if (!SPLIT0 || w > 0) tma_store(&p.hs, src, (ft3 + 9 * w) * 64, r3);
            tma_store(&p.hs72, src + 10240, (ft3 + 9 * w) * 64, r3 + 80);
            bulk_commit();
            bulk_wait0();
            if (TALIGN && w == 0) asm volatile("red.relaxed.gpu.global.max.u32 [%0], %1;" ::"l"(CNT(C_G3, 14)), "r"(gtime32()) : "memory");
            red_cnt(CNT(C_G3 + w, rt3));
            mbar_arrive(BAR(B_LS + 5) + 8 * w);
            mbar_arrive(BAR(B_SF) + 8 * w);
            PROFT(58 + w);
          }
        }
      }
    } else if (warp == 14) {
      if (elect_one()) {
        Cur ws{0, 0};
        mbar_wait(BAR(B_QT), 0);
        if (hasC && PFMODE == 3) {
          constexpr uint32_t junk = sb + OFF_RED + 3 * RBYTES;
          static_assert(OFF_RED + 3 * RBYTES + 17280 <= OFF_MISC, "junk");
          mbar_expect(BAR(B_PF), 2 * (6400 + 17280));
          bulk_load(junk, p.w1p + (size_t)b * 3200, 6400, BAR(B_PF));
          bulk_load(junk, p.w3p + (size_t)b * 8640, 17280, BAR(B_PF));
          bulk_load(junk, p.w2p + (size_t)b * 3200, 6400, BAR(B_PF));
          bulk_load(junk, p.w4p + (size_t)b * 8640, 17280, BAR(B_PF));
        }
        if (hasC && PFMODE == 0) {
          bulk_prefetch(p.w1p + (size_t)b * 3200, 6400);
          bulk_prefetch(p.w3p + (size_t)b * 8640, 17280);
          bulk_prefetch(p.w2p + (size_t)b * 3200, 6400);
          bulk_prefetch(p.w4p + (size_t)b * 8640, 17280);
        }
#pragma unroll 1
        for (int i = 0; i < 20; i++) {
          if (i < WFREE) __nanosleep(400);
          if (i == WFREE) { mbar_wait(BAR(WLATE == 2 ? B_FX : (WLATE ? B_DEP + 2 : B_YT)), 0); mbar_wait(BAR(B_QD), 0); }
          const int e = (int)((i < 10 ? unit_order(1) : unit_order(2)) >> (4 * (i < 10 ? i : i - 10))) & 15, w = e >= 5;
          w_unit(ws, i < 10 ? &p.w1 : &p.w2, (ft + 5 * w) * 64, (e - 5 * w) * 128);
        }
        if (has3) {
#pragma unroll 1
          for (int i = 0; i < 15; i++) {
            const int e = (int)(unit_order(3) >> (4 * i)) & 15, w = (e >= 5) + (e >= 10);
            w_unit(ws, &p.w3, (ft3 + 9 * w) * 64, (e - 5 * w) * 128);
          }
        }
#pragma unroll 1
        for (int i = 0; i < 27; i++) {
          if (i < NWU) mbar_wait(BAR(B_EW) + 8 * ws.slot, ws.par ^ 1); else mbar_wait(BAR(B_E4) + 8 * ws.slot, (i / NWU - 1) & 1);
          mbar_expect(BAR(B_FW) + 8 * ws.slot, WU);
          tma_load3(sb + OFF_W + ws.slot * WU, &p.w4, BAR(B_FW) + 8 * ws.slot, (EXPT & 1) ? 0 : ft * 64, i * 64, 0);
          ws.adv<NWU>(1);
        }
      }
    }
    return;
  }

  const int g = lane >> 2, t = lane & 3, w4 = warp & 3, tid7 = tid & 127;
  const bool leader = tid7 == 0;
  {
    uint2 ka[4], kb[4]; uint32_t pa[4], pb[4];
    if (hasC) {
      conv_fetch(p.ssm, b * 5 + wg, ka, pa);
      if (wg < 2) conv_fetch(p.ssm, b * 5 + wg + 3, kb, pb);
    }
    __syncthreads();
    if (hasC) {
      conv_build(sb, wg, ka, pa, __bfloat162float(p.ssd[b * 5 + wg]));
      if (wg < 2) conv_build(sb, wg + 3, kb, pb, __bfloat162float(p.ssd[b * 5 + wg + 3]));
      fence_async_smem();
    }
  }
  asm volatile("setmaxnreg.inc.sync.aligned.u32 152;");
  if (hasC) {
    bar_sync(1 + wg, 128);
    PROF0(34 + wg);
#pragma unroll 1
    for (int slot = wg; slot < 5; slot += 3) conv_channel(sb, slot, wg, b * 5 + slot, zero, __bfloat162float(p.ssd[b * 5 + slot]), &p.y80, TST);
    if (w4 == 0 && elect_one()) {
      bulk_wait0();
      red_cnt(CNT(C_Y + (b * 5 + wg) / 64, 0));
      if (wg < 2) red_cnt(CNT(C_Y + (b * 5 + wg + 3) / 64, 0));
      mbar_arrive(BAR(B_CD)); PROFT(37 + wg);
    }
    __syncwarp();
  }

  if (wg == 2) {
    if (b < 74) {
      const int ld = b < 54 ? FF : D;
      const __nv_bfloat16* src = (b < 54 ? p.w3p + b * 32 : p.w1p + (b - 54) * 32) + (size_t)(tid7 >> 2) * ld + (lane & 3) * 8;
      float s[8];
#pragma unroll
      for (int i = 0; i < 8; i++) s[i] = 0.f;
#pragma unroll 1
      for (int it = 0; it < 4; it++) {
        uint4 u[5];
#pragma unroll
        for (int i = 0; i < 5; i++) u[i] = ldg128(src + (size_t)(it * 5 + i) * 32 * ld);
#pragma unroll
        for (int i = 0; i < 5; i++) {
          s[0] += blo(u[i].x); s[1] += bhi(u[i].x); s[2] += blo(u[i].y); s[3] += bhi(u[i].y);
          s[4] += blo(u[i].z); s[5] += bhi(u[i].z); s[6] += blo(u[i].w); s[7] += bhi(u[i].w);
        }
      }
#pragma unroll
      for (int i = 0; i < 8; i++) {
#pragma unroll
        for (int o = 4; o < 32; o <<= 1) s[i] += __shfl_xor_sync(0xffffffffu, s[i], o);
      }
      const uint32_t R = sb + OFF_CS;
      if (lane < 4) { sts128f(R + w4 * 128 + lane * 32, s[0], s[1], s[2], s[3]); sts128f(R + w4 * 128 + lane * 32 + 16, s[4], s[5], s[6], s[7]); }
      bar_sync(3, 128);
      if (w4 == 0) {
        float a = 0.f;
#pragma unroll
        for (int i = 0; i < 4; i++) a += __uint_as_float(lds32(R + i * 128 + lane * 4));
        sts32f(R + 512 + lane * 4, a);
        fence_async_smem();
        __syncwarp();
        if (elect_one()) { bulk_store(&g_cs[b * 32], R + 512, 128); bulk_commit(); bulk_wait0(); red_cnt(CNT(C_CS, 0)); PROFT(31); }
        __syncwarp();
      }
    }
    {
      const unsigned e1 = lds32(sb + OFF_EP);
      if (w4 < 3) {
        wait_cnt_w(CNT(C_SQ + rt, 0), e1 * 5);
        { const int r = min(tid7, 79); const float2 s = gather_stats(0, r0 + r); sts64f(sb + OFF_RQ + r * 8, s.x, rsqrtf(s.y + EPS)); }
        bar_sync(7, 96);
        mbar_arrive_if(BAR(B_QS), leader);
        PROF0(28);
        wait_cnt_w(CNT(C_SH + rt, 0), e1 * 10);
        {
          const int r = min(tid7, 79);
          const float2 s = gather_stats(1, r0 + r);
          const float r1 = rsqrtf(s.y + EPS), r2 = 0.5f * r1 * rsqrtf(s.y * r1 * r1 + EPS);
          sts64f(sb + OFF_RP + r * 8, r2, -s.x * r2); sts64f(sb + OFF_RP + 640 + r * 8, r1, -s.x * r1);
        }
      } else {
        wait_cnt_w(CNT(C_CS, 0), e1 * 74);
        const float4 c = ldcg128f(&g_cs[FF + (ft + 5 * (lane >> 4)) * 64 + (lane & 15) * 4]);
        sts128f(sb + OFF_C1 + lane * 16, c.x, c.y, c.z, c.w);
      }
      bar_sync(3, 128);
      mbar_arrive_if(BAR(B_RP), leader);
      PROF0(29);
    }
    if (has3) bar_sync(8, 256);
  }

  float res[40];
  uint32_t hp[20];
  const int f0 = (ft + 5 * wg) * 64;
  const uint32_t stg = sb + OFF_ST + wg * 10240;
  if (wg < 2) {
#pragma unroll
  for (int ph = 0; ph < 3; ph++) {
    uint32_t pk[20];
    if (ph == 0) {
      mbar_wait_u(BAR(B_QT), 0);
      const uint32_t qa = tile_addr(sb + OFF_QT + wg * 10240);
#pragma unroll
      for (int j = 0; j < 10; j += 2) ldsm4t(qa + j * 1024, hp[2 * j], hp[2 * j + 1], hp[2 * j + 2], hp[2 * j + 3]);
      bar_sync(1 + wg, 128);
      mbar_arrive_if(BAR(B_QD), leader);
      mbar_wait_u(BAR(B_QS), 0);
#pragma unroll
      for (int j = 0; j < 10; j++) {
        const float4 st = lds128f(sb + OFF_RQ + (8 * j + 2 * t) * 8);
        res[4 * j] = (blo(hp[2 * j]) - st.x) * st.y; res[4 * j + 1] = (bhi(hp[2 * j]) - st.z) * st.w;
        res[4 * j + 2] = (blo(hp[2 * j + 1]) - st.x) * st.y; res[4 * j + 3] = (bhi(hp[2 * j + 1]) - st.z) * st.w;
      }
      const uint32_t ya = sb + OFF_YT + (64 * wg + 16 * w4 + (lane & 15)) * 160 + (lane >> 4) * 16;
      mbar_wait_u(BAR(B_YT), 0);
      PROF0(40);
#pragma unroll
      for (int j = 0; j < 10; j += 2) {
        uint32_t y[4];
        ldsm4(ya + j * 16, y[0], y[1], y[2], y[3]);
#pragma unroll
        for (int m = 0; m < 4; m++)
          hp[2 * j + m] = pack2(fmaf(res[4 * j + 2 * m], blo(y[m]), blo(hp[2 * j + m])), fmaf(res[4 * j + 2 * m + 1], bhi(y[m]), bhi(hp[2 * j + m])));
      }
#pragma unroll
      for (int i = 0; i < 20; i++) pk[i] = hp[i];
    } else {
      if (ph == 1) mma_g12<1>(res, wg, leader, TST, 64 + 10 * wg); else mma_g12<2>(res, wg, leader, TST, 84 + 10 * wg);
      PROF0(ph == 1 ? 42 + wg : 48 + wg);
      if (ph == 1) {
        mbar_wait_u(BAR(B_RP), 0);
        const float c10 = __uint_as_float(lds32(sb + OFF_C1 + (64 * wg + 16 * w4 + g) * 4)), c11 = __uint_as_float(lds32(sb + OFF_C1 + (64 * wg + 16 * w4 + g + 8) * 4));
        float4 rp[PD1 + 1];
        gelu_prime<0, PD1>(rp, sb + OFF_RP + t * 16);
        gelu_range<0, 10, 10, PD1>(res, pk, rp, sb + OFF_RP + t * 16, c10, c11);
        PROF0(44 + wg);
      } else {
        if (has3 && wg == 1) bar_arrive(8, 256);
#pragma unroll
        for (int i = 0; i < 20; i++) pk[i] = pack2(res[2 * i], res[2 * i + 1]);
      }
    }
    stage_tile<10>(stg, pk);
    fence_async_smem();
    bar_sync(1 + wg, 128);
    if (w4 == 3 && elect_one()) {
      tma_store(&p.h + ph, stg, f0, r0); bulk_commit(); bulk_wait0();
      red_cnt(CNT((ph == 0 ? C_T : (ph == 1 ? C_G1 : C_G2) + 26 * wg) + rt, 0));
      if (ph > 0 || wg == 0) mbar_arrive(BAR(B_LS + (ph == 0 ? 0 : 2 * ph - 1 + wg)));
      PROFT(154 + 2 * ph + wg);
    }
    __syncwarp();
    if (ph == 0) {
#pragma unroll
      for (int i = 0; i < 40; i++) res[i] = 0.f;
    } else if (ph == 1) {
#pragma unroll
      for (int j = 0; j < 10; j++) {
        const float4 rp = lds128f(sb + OFF_RP + 640 + (8 * j + 2 * t) * 8);
        res[4 * j] = fmaf(blo(hp[2 * j]), rp.x, rp.y); res[4 * j + 1] = fmaf(bhi(hp[2 * j]), rp.z, rp.w);
        res[4 * j + 2] = fmaf(blo(hp[2 * j + 1]), rp.x, rp.y); res[4 * j + 3] = fmaf(bhi(hp[2 * j + 1]), rp.z, rp.w);
      }
    } else {
#pragma unroll
      for (int i = 0; i < 20; i++) { res[2 * i] = blo(pk[i]) + blo(hp[i]); res[2 * i + 1] = bhi(pk[i]) + bhi(hp[i]); }
    }
    if (!(ph & 1) && w4 < 3) {
      row_stats<4>(stg, sb + OFF_PS + wg * 640, min(tid7, 79));
      fence_async_smem();
      bar_sync(5 + wg, 96);
      if (w4 == 0 && elect_one()) {
        bulk_store(&g_st[1 + (ph >> 1)][f0 >> 6][r0], sb + OFF_PS + wg * 640, 640); bulk_commit(); bulk_wait0();  red_cnt(CNT((ph == 0 ? C_SH : C_SX) + rt, 0)); }
      __syncwarp();
    }
  }
  }
  if (has3) {
        const int f3 = (ft3 + 9 * wg) * 64;
        const float cs0 = ldcg32f(&g_cs[f3 + 16 * w4 + g]), cs1 = ldcg32f(&g_cs[f3 + 16 * w4 + g + 8]);
        float acc[76];
#pragma unroll
        for (int i = 0; i < 76; i++) acc[i] = 0.f;
        mma_g3(acc, wg, leader, TST, 104 + 10 * wg);
        PROF0(52 + wg);
        mbar_wait_u(BAR(B_RP3), 0);
        if (CHAIN && wg >= CHAIN) mbar_wait_u(BAR(B_GC + wg - 1), 0);
        const uint32_t sta = tile_addr(sb + OFF_ST);
        uint32_t pq[38];
        float4 rp[PD3 + 1];
        gelu_prime<0, PD3>(rp, sb + OFF_RP3 + t * 16);
        gelu_range<0, 10, 19, PD3>(acc, pq, rp, sb + OFF_RP3 + t * 16, cs0, cs1);
        if (SPLIT0 && wg == 0) {
#pragma unroll
          for (int jj = 0; jj < 10; jj += 2) stsm4t(sta + jj * 1024, pq[2 * jj], pq[2 * jj + 1], pq[2 * jj + 2], pq[2 * jj + 3]);
          fence_async_smem();
          bar_sync(1, 128);
          mbar_arrive_if(BAR(B_SG + 3), leader);
        }
        gelu_range<10, 19, 19, PD3>(acc, pq, rp, sb + OFF_RP3 + t * 16, cs0, cs1);
        if (CHAIN) mbar_arrive_if(BAR(B_GC + (wg & 1)), leader && wg < 2);
        PROF0(55 + wg);
        if (wg > 0) mbar_wait_u(BAR(B_SF + wg - 1), 0);
        if (!SPLIT0 || wg > 0) {
#pragma unroll
          for (int jj = 0; jj < 10; jj += 2) stsm4t(sta + jj * 1024, pq[2 * jj], pq[2 * jj + 1], pq[2 * jj + 2], pq[2 * jj + 3]);
        }
#pragma unroll
        for (int jj = 10; jj < 18; jj += 2) stsm4t(sta + jj * 1024, pq[2 * jj], pq[2 * jj + 1], pq[2 * jj + 2], pq[2 * jj + 3]);
        stsm2t(sta + 18 * 1024 - (lane >> 4) * 1024, pq[36], pq[37]);
        fence_async_smem();
        bar_sync(1 + wg, 128);
        mbar_arrive_if(BAR(B_SG + wg), leader);
      }
  if (wg < 2) {
    if (GSYNC & 8) mbar_wait_u(BAR(B_DEP + 10), 0);
    PROF0(41);
    mma_g4(res, wg, has3 ? 35 : 20, leader, TST, 134 + 10 * wg);
    PROF0(61);
    uint32_t pk[20];
#pragma unroll
    for (int i = 0; i < 20; i++) pk[i] = pack2(res[2 * i], res[2 * i + 1]);
    if (has3) mbar_wait_u(BAR(B_SF + 2), 0);
    stage_tile<10>(stg, pk);
    fence_async_smem();
    bar_sync(1 + wg, 128);
    if (w4 == 0 && elect_one()) {
      tma_store(&p.out, stg, f0, r0); bulk_commit(); bulk_wait0(); PROFT(62 + wg);
    }
  }
}

typedef CUresult (*EncFn)(CUtensorMap*, CUtensorMapDataType, cuuint32_t, void*, const cuuint64_t*, const cuuint64_t*, const cuuint32_t*,
                          const cuuint32_t*, CUtensorMapInterleave, CUtensorMapSwizzle, CUtensorMapL2promotion, CUtensorMapFloatOOBfill);
void make_map(EncFn enc, CUtensorMap* tm, const void* ptr, int cols, int rows, int bc, int br, CUtensorMapSwizzle sw) {
  cuuint64_t gd[2] = {(cuuint64_t)cols, (cuuint64_t)rows}, gs[1] = {(cuuint64_t)cols * 2};
  cuuint32_t bd[2] = {(cuuint32_t)bc, (cuuint32_t)br}, es[2] = {1, 1};
  enc(tm, CU_TENSOR_MAP_DATA_TYPE_BFLOAT16, 2, const_cast<void*>(ptr), gd, gs, bd, es, CU_TENSOR_MAP_INTERLEAVE_NONE, sw,
      CU_TENSOR_MAP_L2_PROMOTION_L2_128B, CU_TENSOR_MAP_FLOAT_OOB_FILL_NONE);
}
void make_map2(EncFn enc, CUtensorMap* tm, const void* ptr, int cols) {
  cuuint64_t gd[3] = {64, (cuuint64_t)S, (cuuint64_t)cols / 64}, gs[2] = {(cuuint64_t)cols * 2, 128};
  cuuint32_t bd[3] = {64, 80, 2}, es[3] = {1, 1, 1};
  enc(tm, CU_TENSOR_MAP_DATA_TYPE_BFLOAT16, 3, const_cast<void*>(ptr), gd, gs, bd, es, CU_TENSOR_MAP_INTERLEAVE_NONE, CU_TENSOR_MAP_SWIZZLE_128B,
      CU_TENSOR_MAP_L2_PROMOTION_L2_128B, CU_TENSOR_MAP_FLOAT_OOB_FILL_NONE);
}
template <class T> void* sym_addr(T& s) { void* a = nullptr; cudaGetSymbolAddress(&a, s); return a; }

}

extern "C" void kernel_launch(void* const* d_in, const int* in_sizes, int n_in, void* d_out, int out_size) {
  (void)in_sizes; (void)n_in; (void)out_size;
  void* fn = nullptr; cudaDriverEntryPointQueryResult qr;
  cudaGetDriverEntryPoint("cuTensorMapEncodeTiled", &fn, cudaEnableDefault, &qr);
  EncFn enc = (EncFn)fn;
  Params p;
  typedef const __nv_bfloat16* BP;
  p.q = (BP)d_in[0]; p.k = (BP)d_in[1]; p.v = (BP)d_in[2]; p.shk = (BP)d_in[3]; p.ssm = (BP)d_in[4]; p.ssd = (BP)d_in[5];
  p.w1p = (BP)d_in[7]; p.w2p = (BP)d_in[8]; p.w3p = (BP)d_in[9]; p.w4p = (BP)d_in[10];
  const CUtensorMapSwizzle S128 = CU_TENSOR_MAP_SWIZZLE_128B, S64 = CU_TENSOR_MAP_SWIZZLE_64B, S0 = CU_TENSOR_MAP_SWIZZLE_NONE;
  make_map(enc, &p.w1, p.w1p, D, D, 64, 128, S128);
  make_map(enc, &p.w2, p.w2p, D, D, 64, 128, S128);
  make_map(enc, &p.w3, p.w3p, FF, D, 64, 128, S128);
  {
    cuuint64_t gd[3] = {320, (cuuint64_t)FF, 2}, gs[2] = {(cuuint64_t)D * 2, 640};
    cuuint32_t bd[3] = {64, 64, 2}, es[3] = {1, 1, 1};
    enc(&p.w4, CU_TENSOR_MAP_DATA_TYPE_BFLOAT16, 3, const_cast<__nv_bfloat16*>(p.w4p), gd, gs, bd, es, CU_TENSOR_MAP_INTERLEAVE_NONE, S128,
        CU_TENSOR_MAP_L2_PROMOTION_L2_128B, CU_TENSOR_MAP_FLOAT_OOB_FILL_NONE);
  }
  {
    cuuint64_t gd[4] = {1024, 80, 2, 8}, gs[3] = {32768, 2048, 4096};
    cuuint32_t bd[4] = {80, 8, 2, 4}, es[4] = {1, 1, 1, 1};
    enc(&p.kv, CU_TENSOR_MAP_DATA_TYPE_BFLOAT16, 4, sym_addr(g_kvT), gd, gs, bd, es, CU_TENSOR_MAP_INTERLEAVE_NONE, S0,
        CU_TENSOR_MAP_L2_PROMOTION_NONE, CU_TENSOR_MAP_FLOAT_OOB_FILL_NONE);
  }
  make_map(enc, &p.q80, p.q, D, S, 64, 80, S128);
  {
    cuuint64_t gd[3] = {80, (cuuint64_t)D, 26}, gs[2] = {160, (cuuint64_t)D * 160};
    cuuint32_t bd[3] = {80, 1, 26}, es[3] = {1, 1, 1};
    enc(&p.y80, CU_TENSOR_MAP_DATA_TYPE_BFLOAT16, 3, sym_addr(g_yB), gd, gs, bd, es, CU_TENSOR_MAP_INTERLEAVE_NONE, S0,
        CU_TENSOR_MAP_L2_PROMOTION_NONE, CU_TENSOR_MAP_FLOAT_OOB_FILL_NONE);
  }
  make_map(enc, &p.h, sym_addr(g_h), D, S, 64, 80, S128);
  make_map(enc, &p.h1, sym_addr(g_h1), D, S, 64, 80, S128);
  make_map(enc, &p.h1n, sym_addr(g_h1), D, S, 32, 80, S64);
  make_map(enc, &p.x1s, sym_addr(g_x1), D, S, 64, 80, S128);
  make_map(enc, &p.x1l, sym_addr(g_x1), D, S, 64, 152, S128);
  make_map(enc, &p.hs, sym_addr(g_hid), FF, S, 64, 80, S128);
  make_map(enc, &p.hs72, sym_addr(g_hid), FF, S, 64, 72, S128);
  make_map2(enc, &p.hl2, sym_addr(g_hid), FF);
  make_map2(enc, &p.h2, sym_addr(g_h), D);
  make_map(enc, &p.out, d_out, D, S, 64, 80, S128);
  cudaFuncSetAttribute(fused_kernel, cudaFuncAttributeMaxDynamicSharedMemorySize, SMEM_BYTES);
  fused_kernel<<<NCTA, NTHR, SMEM_BYTES, cudaStreamPerThread>>>(p, 0u);
}
```
